```python
import torch

def _softmax(x, axis=-1):
    return torch.softmax(x, dim=axis)

def _gelu(x):
    return torch.nn.functional.gelu(x, approximate='tanh')

def _silu(x):
    return torch.nn.functional.silu(x)

def _sigmoid(x):
    return torch.sigmoid(x)

def _layernorm(x, axis=-1, eps=1e-05):
    m = x.mean(dim=axis, keepdim=True)
    v = x.var(dim=axis, keepdim=True, unbiased=False)
    return (x - m) / torch.sqrt(v + eps)

def _scatter_add(tgt, idx, src, axis=0):
    return tgt.clone().index_add_(axis, idx, src)

def _segment_sum(src, seg, n):
    out = torch.zeros((n,) + src.shape[1:], dtype=src.dtype)
    return out.index_add_(0, seg, src)

def _pad(x, pw):
    flat = tuple((v for pair in reversed(pw) for v in pair))
    return torch.nn.functional.pad(x, flat)
kernel_name = 'adaLN_cond__ssm_conv_s4d__glu_gated_geglu__prompt'

def setup_inputs():

    _w = lambda a: (lambda t: t.to(torch.bfloat16) if t.is_floating_point() else t)(torch.as_tensor(a))

    def _A_setup():
        Bsz, L, D, N = (1, 2048, 640, 128)
        return {'u': _w((lambda *s: torch.randn(*s, dtype=torch.bfloat16) * 0.05)(Bsz, L, D)), 'log_A_real': _w((lambda *s: torch.randn(*s, dtype=torch.bfloat16) * 3.2)(D, N) * 0.5), 'A_imag': _w((lambda *s: torch.randn(*s, dtype=torch.bfloat16) * 0.05)(D, N) * 3.14), 'C_real': _w((lambda *s: torch.randn(*s, dtype=torch.bfloat16) * 0.4)(D, N) / N ** 0.5), 'C_imag': _w((lambda *s: torch.randn(*s, dtype=torch.bfloat16) * 0.4)(D, N) / N ** 0.5), 'log_dt': _w((lambda *s: torch.randn(*s, dtype=torch.bfloat16) * 0.05)(D) * 0.5 - 4.0), 'D_skip': _w((lambda *s: torch.randn(*s, dtype=torch.bfloat16) * 0.05)(D))}
    _A_in = _A_setup()

    def _B_setup():
        B, S, Dm, Df = (1, 2048, 640, 1728)
        return {'x': _w((lambda *s: torch.randn(*s, dtype=torch.bfloat16) * 0.05)(B, S, Dm)), 'w_gate': _w((lambda *s: torch.randn(*s, dtype=torch.bfloat16) * 0.8)(Dm, Df) * Dm ** (-0.5)), 'w_up': _w((lambda *s: torch.randn(*s, dtype=torch.bfloat16) * 0.8)(Dm, Df) * Dm ** (-0.5)), 'w_down': _w((lambda *s: torch.randn(*s, dtype=torch.bfloat16) * 0.8)(Df, Dm) * Df ** (-0.5))}
    _B_in = _B_setup()
    return {'A_u': _A_in['u'], 'A_log_A_real': _A_in['log_A_real'], 'A_A_imag': _A_in['A_imag'], 'A_C_real': _A_in['C_real'], 'A_C_imag': _A_in['C_imag'], 'A_log_dt': _A_in['log_dt'], 'A_D_skip': _A_in['D_skip'], 'B_x': _B_in['x'], 'B_w_gate': _B_in['w_gate'], 'B_w_up': _B_in['w_up'], 'B_w_down': _B_in['w_down'], 'c': _w((lambda *s: torch.randn(*s, dtype=torch.bfloat16) * 0.2)(1, 640) * 8.0), 'w_mod': _w((lambda *s: torch.randn(*s, dtype=torch.bfloat16) * 0.2)(640, 6 * 640) * 640 ** (-0.5) * 8.0)}

def reference(A_u, A_log_A_real, A_A_imag, A_C_real, A_C_imag, A_log_dt, A_D_skip, B_x, B_w_gate, B_w_up, B_w_down, c, w_mod):

    def _A_ref(u, log_A_real, A_imag, C_real, C_imag, log_dt, D_skip):
        L = u.shape[1]
        dt = torch.exp(log_dt)
        A = -torch.exp(log_A_real) + 1j * A_imag
        C = (C_real + 1j * C_imag) * dt[:, None]
        pos = (lambda x, dt: x.to(dt))(torch.arange(L), log_dt.dtype)
        P = torch.exp((A * dt[:, None])[:, :, None] * pos[None, None, :])
        K = 2.0 * torch.einsum('dn,dnl->dl', C, P).real
        L2 = 2 * L
        u_t = (lambda x, *d: x.permute(*d))(u, 0, 2, 1)
        Kf = (lambda x, *a, **k: torch.fft.rfft(x.float(), *a, **k))(K, L2)
        Uf = (lambda x, *a, **k: torch.fft.rfft(x.float(), *a, **k))(u_t, L2)
        y = (lambda x, *a, **k: torch.fft.irfft(x, *a, **k).to(torch.bfloat16))(Uf * Kf[None, :, :], L2)[:, :, :L]
        y = (lambda x, *d: x.permute(*d))(y, 0, 2, 1)
        return y + u * D_skip[None, None, :]

    def _B_ref(x, w_gate, w_up, w_down):
        g = torch.einsum('bsd,df->bsf', x, w_gate)
        u = torch.einsum('bsd,df->bsf', x, w_up)
        h = _gelu(g) * u
        return torch.einsum('bsf,fd->bsd', h, w_down)
    x = A_u
    mod = (_silu(c) @ w_mod).reshape(c.shape[0], 6, 1, -1)
    sa, ca, ga, sb, cb, gb = (mod[:, 0].clone(), mod[:, 1].clone(), mod[:, 2].clone(), mod[:, 3].clone(), mod[:, 4].clone(), mod[:, 5].clone())
    h = _layernorm(x, axis=-1) * (1 + ca) + sa
    x = x + ga * _A_ref(h, A_log_A_real, A_A_imag, A_C_real, A_C_imag, A_log_dt, A_D_skip)
    h = _layernorm(x, axis=-1) * (1 + cb) + sb
    x = x + gb * _B_ref(h, B_w_gate, B_w_up, B_w_down)
    return x
```

```cpp
#include <cuda_runtime.h>
#include <cuda.h>
#include <cuda_bf16.h>
#include <cuda_fp16.h>
#include <stdint.h>
#include <string.h>

namespace {

constexpr int LSEQ = 2048, DM = 640, DF = 1728;
constexpr int NCTA = 128, NTHR = 384;
constexpr int FA = 120, FB = 96;
constexpr int NA = 2 * FA, NB = 2 * FB;
constexpr int TA_ = FA / 8, TB_ = FB / 8;
constexpr int BLOB_A = DM * NA, BLOB_B = DM * NB;
constexpr int S2A = 4 * FA / 32, S2B = 4 * FB / 32, S2 = S2A + S2B;

__device__ __align__(1024) __nv_bfloat16 g_xT[DM * LSEQ];
__device__ __align__(1024) __half        g_vT[DM * LSEQ];
__device__ __align__(1024) __nv_bfloat16 g_x1T[DM * LSEQ];
__device__ __align__(1024) __nv_bfloat16 g_Wp[DM * 2 * DF];
__device__ __align__(1024) __nv_bfloat16 g_h[LSEQ * DF];
__device__ __align__(1024) float2 g_cp[2 * DF];
__device__ __align__(1024) float  g_mod[6 * DM];
__device__ __align__(1024) float2 g_st2[LSEQ];
__device__ __align__(1024) unsigned g_cnt[128 * 32];
#define STAMP(i)
constexpr int C_BAR1 = 0, C_MOD2 = 1, C_BAR2 = 2, C_ST = 8, C_HA = 32, C_HB = 64;

constexpr int SM_A = 0;
constexpr int SM_B = 163840;
constexpr int BST = 32 * NA * 2;
constexpr int SM_MISC = SM_B + 4 * BST;
constexpr int SLOT2 = 18432;
constexpr int SM_RES = 147456;
constexpr int SM_XCH = SM_RES + 20480;
constexpr int SM_BARS = SM_MISC;
constexpr int SM_ST2 = SM_MISC + 512;
constexpr int SM_CP = SM_ST2 + 1024;
constexpr int SM_RED = SM_CP + 3456;
constexpr int SM_END = SM_RED + 1536;
constexpr int SMEM_BYTES = SM_END;
static_assert(SMEM_BYTES <= 232448, "smem");
constexpr int XROW = 1296;
constexpr int SM_XS = 0;
constexpr int SM_VS = SM_XS + 16 * XROW;
constexpr int HPL = 136 * 16;
constexpr int SM_X = 0;
constexpr int SM_H = 20480;
constexpr int SM_WB = 42240;
constexpr int SM_KH = SM_WB + 8 * 4672 + 4 * 6144;
constexpr int PTW = 2080;
constexpr int SM_PT = SM_KH + 5 * 1296;
static_assert(SM_PT + 5 * PTW * 4 <= SM_B, "front smem");
__device__ __forceinline__ int wblk(int w) { return SM_WB + (w < 8 ? w * 4672 : 8 * 4672 + (w - 8) * 6144); }

enum { B_DATA = 0, B_FULLA = 1, B_FULLB = 11, B_EMPTYB = 15, B_FREEA = 19, B_FULL2 = 29, B_EMPTY2 = 37,
       B_STATS = 45, B_CP = 46, B_HA = 47, B_HB = 48, B_RES = 49, B_XRDY = 50, B_XFULL = 51, B_NUM = 52 };

__device__ __forceinline__ uint32_t smem_u32(const void* p) { return (uint32_t)__cvta_generic_to_shared(p); }
__device__ __forceinline__ void mbar_init(uint32_t bar, int cnt) { asm volatile("mbarrier.init.shared::cta.b64 [%0], %1;" ::"r"(bar), "r"(cnt)); }
__device__ __forceinline__ void mbar_arrive(uint32_t bar) { asm volatile("mbarrier.arrive.shared::cta.b64 _, [%0];" ::"r"(bar) : "memory"); }
__device__ __forceinline__ void mbar_expect_tx(uint32_t bar, uint32_t bytes) { asm volatile("mbarrier.arrive.expect_tx.shared::cta.b64 _, [%0], %1;" ::"r"(bar), "r"(bytes) : "memory"); }
__device__ __forceinline__ void mbar_wait(uint32_t bar, uint32_t parity) {
  asm volatile("{\n.reg .pred p;\n.reg .u32 c;\nmov.u32 c, 0;\nLW:\nmbarrier.try_wait.parity.shared::cta.b64 p, [%0], %1;\n@p bra LD;\nadd.u32 c, c, 1;\nsetp.lt.u32 p, c, 2000000;\n@p bra LW;\ntrap;\nLD:\n}" ::"r"(bar), "r"(parity) : "memory");
}
__device__ __forceinline__ void mbar_wait_cluster(uint32_t bar, uint32_t parity) {
  asm volatile("{\n.reg .pred p;\n.reg .u32 c;\nmov.u32 c, 0;\nLW:\nmbarrier.try_wait.parity.acquire.cluster.shared::cta.b64 p, [%0], %1;\n@p bra LD;\nadd.u32 c, c, 1;\nsetp.lt.u32 p, c, 2000000;\n@p bra LW;\ntrap;\nLD:\n}" ::"r"(bar), "r"(parity) : "memory");
}
__device__ __forceinline__ uint32_t mapa(uint32_t a, uint32_t cta) { uint32_t r; asm volatile("mapa.shared::cluster.u32 %0, %1, %2;" : "=r"(r) : "r"(a), "r"(cta)); return r; }
__device__ __forceinline__ void bulk_g2s(uint32_t dst, const void* src, uint32_t bytes, uint32_t bar) {
  asm volatile("cp.async.bulk.shared::cluster.global.mbarrier::complete_tx::bytes [%0], [%1], %2, [%3];" ::"r"(dst), "l"(src), "r"(bytes), "r"(bar) : "memory");
}
__device__ __forceinline__ void bulk_s2g(void* dst, uint32_t src, uint32_t bytes) {
  asm volatile("cp.async.bulk.global.shared::cta.bulk_group [%0], [%1], %2;" ::"l"(dst), "r"(src), "r"(bytes) : "memory");
}
__device__ __forceinline__ void tma2d(uint32_t dst, const CUtensorMap* tm, int c0, int c1, uint32_t bar) {
  asm volatile("cp.async.bulk.tensor.2d.shared::cluster.global.mbarrier::complete_tx::bytes [%0], [%1, {%3, %4}], [%2];" ::"r"(dst), "l"(tm), "r"(bar), "r"(c0), "r"(c1) : "memory");
}
__device__ __forceinline__ void tma3d(uint32_t dst, const CUtensorMap* tm, int c0, int c1, int c2, uint32_t bar) {
  asm volatile("cp.async.bulk.tensor.3d.shared::cluster.global.mbarrier::complete_tx::bytes [%0], [%1, {%3, %4, %5}], [%2];" ::"r"(dst), "l"(tm), "r"(bar), "r"(c0), "r"(c1), "r"(c2) : "memory");
}
__device__ __forceinline__ void fence_async() { asm volatile("fence.proxy.async;" ::: "memory"); }
__device__ __forceinline__ void fence_async_smem() { asm volatile("fence.proxy.async.shared::cta;" ::: "memory"); }
__device__ __forceinline__ void nbar(int id, int n) { asm volatile("bar.sync %0, %1;" ::"r"(id), "r"(n) : "memory"); }
__device__ __forceinline__ void red_release(unsigned* p, unsigned v) { asm volatile("red.release.gpu.global.add.u32 [%0], %1;" ::"l"(p), "r"(v) : "memory"); }
__device__ __forceinline__ void poll_ge(const unsigned* p, unsigned target) {
  unsigned v; int it = 0;
  do { asm volatile("ld.acquire.gpu.global.u32 %0, [%1];" : "=r"(v) : "l"(p) : "memory"); if (++it > 4000000) __trap(); } while ((int)(v - target) < 0);
}
__device__ __forceinline__ float ldg_relaxed(const float* p) { float v; asm volatile("ld.relaxed.gpu.global.f32 %0, [%1];" : "=f"(v) : "l"(p) : "memory"); return v; }
__device__ __forceinline__ void wg_fence() { asm volatile("wgmma.fence.sync.aligned;" ::: "memory"); }
__device__ __forceinline__ void wg_commit() { asm volatile("wgmma.commit_group.sync.aligned;" ::: "memory"); }
template <int N> __device__ __forceinline__ void wg_wait() { asm volatile("wgmma.wait_group.sync.aligned %0;" ::"n"(N) : "memory"); }
__device__ __forceinline__ uint64_t mkdesc(uint32_t addr, uint32_t lbo, uint32_t sbo, int swz) {
  return (uint64_t)((addr & 0x3FFFF) >> 4) | ((uint64_t)(lbo >> 4) << 16) | ((uint64_t)(sbo >> 4) << 32) | ((uint64_t)swz << 62);
}
__device__ __forceinline__ void ldsm4(uint32_t a, uint32_t& r0, uint32_t& r1, uint32_t& r2, uint32_t& r3) {
  asm volatile("ldmatrix.sync.aligned.m8n8.x4.shared.b16 {%0,%1,%2,%3}, [%4];" : "=r"(r0), "=r"(r1), "=r"(r2), "=r"(r3) : "r"(a) : "memory");
}
__device__ __forceinline__ void ldsm4t(uint32_t a, uint32_t& r0, uint32_t& r1, uint32_t& r2, uint32_t& r3) {
  asm volatile("ldmatrix.sync.aligned.m8n8.x4.trans.shared.b16 {%0,%1,%2,%3}, [%4];" : "=r"(r0), "=r"(r1), "=r"(r2), "=r"(r3) : "r"(a) : "memory");
}
__device__ __forceinline__ void stsm4t(uint32_t a, uint32_t r0, uint32_t r1, uint32_t r2, uint32_t r3) {
  asm volatile("stmatrix.sync.aligned.m8n8.x4.trans.shared.b16 [%0], {%1,%2,%3,%4};" ::"r"(a), "r"(r0), "r"(r1), "r"(r2), "r"(r3) : "memory");
}
__device__ __forceinline__ void stsm4(uint32_t a, uint32_t r0, uint32_t r1, uint32_t r2, uint32_t r3) {
  asm volatile("stmatrix.sync.aligned.m8n8.x4.shared.b16 [%0], {%1,%2,%3,%4};" ::"r"(a), "r"(r0), "r"(r1), "r"(r2), "r"(r3) : "memory");
}
__device__ __forceinline__ void mma_f16(float (&d)[4], uint32_t a0, uint32_t a1, uint32_t a2, uint32_t a3, uint32_t b0, uint32_t b1) {
  asm volatile("mma.sync.aligned.m16n8k16.row.col.f32.f16.f16.f32 {%0,%1,%2,%3},{%4,%5,%6,%7},{%8,%9},{%0,%1,%2,%3};"
               : "+f"(d[0]), "+f"(d[1]), "+f"(d[2]), "+f"(d[3]) : "r"(a0), "r"(a1), "r"(a2), "r"(a3), "r"(b0), "r"(b1));
}
__device__ __forceinline__ uint32_t lds32(uint32_t a) { uint32_t v; asm volatile("ld.shared.u32 %0, [%1];" : "=r"(v) : "r"(a) : "memory"); return v; }
__device__ __forceinline__ float4 lds128f(uint32_t a) { float4 v; asm volatile("ld.shared.v4.f32 {%0,%1,%2,%3}, [%4];" : "=f"(v.x), "=f"(v.y), "=f"(v.z), "=f"(v.w) : "r"(a) : "memory"); return v; }
__device__ __forceinline__ uint4 lds128(uint32_t a) { uint4 v; asm volatile("ld.shared.v4.u32 {%0,%1,%2,%3}, [%4];" : "=r"(v.x), "=r"(v.y), "=r"(v.z), "=r"(v.w) : "r"(a) : "memory"); return v; }
__device__ __forceinline__ void sts128f(uint32_t a, float x, float y, float z, float w) { asm volatile("st.shared.v4.f32 [%0], {%1,%2,%3,%4};" ::"r"(a), "f"(x), "f"(y), "f"(z), "f"(w) : "memory"); }
__device__ __forceinline__ void sts128(uint32_t a, uint4 v) { asm volatile("st.shared.v4.u32 [%0], {%1,%2,%3,%4};" ::"r"(a), "r"(v.x), "r"(v.y), "r"(v.z), "r"(v.w) : "memory"); }
__device__ __forceinline__ uint32_t pack_h2(float lo, float hi) { uint32_t r; asm("cvt.rn.f16x2.f32 %0, %1, %2;" : "=r"(r) : "f"(hi), "f"(lo)); return r; }
__device__ __forceinline__ uint32_t pack_bf2(float lo, float hi) { uint32_t r; asm("cvt.rn.bf16x2.f32 %0, %1, %2;" : "=r"(r) : "f"(hi), "f"(lo)); return r; }
__device__ __forceinline__ float bf_lo(uint32_t v) { return __uint_as_float(v << 16); }
__device__ __forceinline__ float bf_hi(uint32_t v) { return __uint_as_float(v & 0xffff0000u); }
__device__ __forceinline__ float bf16r(float x) { return __bfloat162float(__float2bfloat16_rn(x)); }
__device__ __forceinline__ float bfld(const __nv_bfloat16* p) { return __uint_as_float((uint32_t)__ldg((const unsigned short*)p) << 16); }
__device__ __forceinline__ float ex2f(float x) { float r; asm("ex2.approx.ftz.f32 %0, %1;" : "=f"(r) : "f"(x)); return r; }
__device__ __forceinline__ float tanhf_(float x) { float r; asm("tanh.approx.f32 %0, %1;" : "=f"(r) : "f"(x)); return r; }
struct cf { float r, i; };
__device__ __forceinline__ cf cmul(cf a, cf b) { cf o; o.r = fmaf(a.r, b.r, -(a.i * b.i)); o.i = fmaf(a.r, b.i, a.i * b.r); return o; }
__device__ __forceinline__ cf csq(cf a) { cf o; o.r = fmaf(a.r, a.r, -(a.i * a.i)); o.i = (a.r * a.i) * 2.0f; return o; }
__device__ __forceinline__ cf cpow_direct(float lr2, float th, float p) {
  float m = ex2f(lr2 * p); float a = th * p; a = (a - rintf(a)) * 6.283185307179586f;
  cf o; o.r = m * __cosf(a); o.i = m * __sinf(a); return o;
}
__device__ __forceinline__ int krank(int l) {
  int k = max(0, 24 - __clz(l | 1));
  int j = (l + ((1 << k) >> 1) - (k > 0) + ((l >> k) & (k > 0))) >> k;
  return 128 * k + j;
}

template<int N> struct WG;
template<int TA, int TB> __device__ __forceinline__ void wgmma_ss_240(float (&d)[120], uint64_t da, uint64_t db, int sd) {
  asm volatile("{\n.reg .pred p;\nsetp.ne.b32 p, %122, 0;\n"
  "wgmma.mma_async.sync.aligned.m64n240k16.f32.bf16.bf16 {%0, %1, %2, %3, %4, %5, %6, %7, %8, %9, %10, %11, %12, %13, %14, %15, %16, %17, %18, %19, %20, %21, %22, %23, %24, %25, %26, %27, %28, %29, %30, %31, %32, %33, %34, %35, %36, %37, %38, %39, %40, %41, %42, %43, %44, %45, %46, %47, %48, %49, %50, %51, %52, %53, %54, %55, %56, %57, %58, %59, %60, %61, %62, %63, %64, %65, %66, %67, %68, %69, %70, %71, %72, %73, %74, %75, %76, %77, %78, %79, %80, %81, %82, %83, %84, %85, %86, %87, %88, %89, %90, %91, %92, %93, %94, %95, %96, %97, %98, %99, %100, %101, %102, %103, %104, %105, %106, %107, %108, %109, %110, %111, %112, %113, %114, %115, %116, %117, %118, %119}, %120, %121, p, 1, 1, %123, %124;\n}\n"
  : "+f"(d[0]), "+f"(d[1]), "+f"(d[2]), "+f"(d[3]), "+f"(d[4]), "+f"(d[5]), "+f"(d[6]), "+f"(d[7]), "+f"(d[8]), "+f"(d[9]), "+f"(d[10]), "+f"(d[11]), "+f"(d[12]), "+f"(d[13]), "+f"(d[14]), "+f"(d[15]), "+f"(d[16]), "+f"(d[17]), "+f"(d[18]), "+f"(d[19]), "+f"(d[20]), "+f"(d[21]), "+f"(d[22]), "+f"(d[23]), "+f"(d[24]), "+f"(d[25]), "+f"(d[26]), "+f"(d[27]), "+f"(d[28]), "+f"(d[29]), "+f"(d[30]), "+f"(d[31]), "+f"(d[32]), "+f"(d[33]), "+f"(d[34]), "+f"(d[35]), "+f"(d[36]), "+f"(d[37]), "+f"(d[38]), "+f"(d[39]), "+f"(d[40]), "+f"(d[41]), "+f"(d[42]), "+f"(d[43]), "+f"(d[44]), "+f"(d[45]), "+f"(d[46]), "+f"(d[47]), "+f"(d[48]), "+f"(d[49]), "+f"(d[50]), "+f"(d[51]), "+f"(d[52]), "+f"(d[53]), "+f"(d[54]), "+f"(d[55]), "+f"(d[56]), "+f"(d[57]), "+f"(d[58]), "+f"(d[59]), "+f"(d[60]), "+f"(d[61]), "+f"(d[62]), "+f"(d[63]), "+f"(d[64]), "+f"(d[65]), "+f"(d[66]), "+f"(d[67]), "+f"(d[68]), "+f"(d[69]), "+f"(d[70]), "+f"(d[71]), "+f"(d[72]), "+f"(d[73]), "+f"(d[74]), "+f"(d[75]), "+f"(d[76]), "+f"(d[77]), "+f"(d[78]), "+f"(d[79]), "+f"(d[80]), "+f"(d[81]), "+f"(d[82]), "+f"(d[83]), "+f"(d[84]), "+f"(d[85]), "+f"(d[86]), "+f"(d[87]), "+f"(d[88]), "+f"(d[89]), "+f"(d[90]), "+f"(d[91]), "+f"(d[92]), "+f"(d[93]), "+f"(d[94]), "+f"(d[95]), "+f"(d[96]), "+f"(d[97]), "+f"(d[98]), "+f"(d[99]), "+f"(d[100]), "+f"(d[101]), "+f"(d[102]), "+f"(d[103]), "+f"(d[104]), "+f"(d[105]), "+f"(d[106]), "+f"(d[107]), "+f"(d[108]), "+f"(d[109]), "+f"(d[110]), "+f"(d[111]), "+f"(d[112]), "+f"(d[113]), "+f"(d[114]), "+f"(d[115]), "+f"(d[116]), "+f"(d[117]), "+f"(d[118]), "+f"(d[119])
  : "l"(da), "l"(db), "r"(sd), "n"(TA), "n"(TB));
}
template<> struct WG<240> { template<int TA,int TB> static __device__ __forceinline__ void ss(float (&d)[120], uint64_t da, uint64_t db, int sd) { wgmma_ss_240<TA,TB>(d,da,db,sd); } };
template<int TA, int TB> __device__ __forceinline__ void wgmma_ss_192(float (&d)[96], uint64_t da, uint64_t db, int sd) {
  asm volatile("{\n.reg .pred p;\nsetp.ne.b32 p, %98, 0;\n"
  "wgmma.mma_async.sync.aligned.m64n192k16.f32.bf16.bf16 {%0, %1, %2, %3, %4, %5, %6, %7, %8, %9, %10, %11, %12, %13, %14, %15, %16, %17, %18, %19, %20, %21, %22, %23, %24, %25, %26, %27, %28, %29, %30, %31, %32, %33, %34, %35, %36, %37, %38, %39, %40, %41, %42, %43, %44, %45, %46, %47, %48, %49, %50, %51, %52, %53, %54, %55, %56, %57, %58, %59, %60, %61, %62, %63, %64, %65, %66, %67, %68, %69, %70, %71, %72, %73, %74, %75, %76, %77, %78, %79, %80, %81, %82, %83, %84, %85, %86, %87, %88, %89, %90, %91, %92, %93, %94, %95}, %96, %97, p, 1, 1, %99, %100;\n}\n"
  : "+f"(d[0]), "+f"(d[1]), "+f"(d[2]), "+f"(d[3]), "+f"(d[4]), "+f"(d[5]), "+f"(d[6]), "+f"(d[7]), "+f"(d[8]), "+f"(d[9]), "+f"(d[10]), "+f"(d[11]), "+f"(d[12]), "+f"(d[13]), "+f"(d[14]), "+f"(d[15]), "+f"(d[16]), "+f"(d[17]), "+f"(d[18]), "+f"(d[19]), "+f"(d[20]), "+f"(d[21]), "+f"(d[22]), "+f"(d[23]), "+f"(d[24]), "+f"(d[25]), "+f"(d[26]), "+f"(d[27]), "+f"(d[28]), "+f"(d[29]), "+f"(d[30]), "+f"(d[31]), "+f"(d[32]), "+f"(d[33]), "+f"(d[34]), "+f"(d[35]), "+f"(d[36]), "+f"(d[37]), "+f"(d[38]), "+f"(d[39]), "+f"(d[40]), "+f"(d[41]), "+f"(d[42]), "+f"(d[43]), "+f"(d[44]), "+f"(d[45]), "+f"(d[46]), "+f"(d[47]), "+f"(d[48]), "+f"(d[49]), "+f"(d[50]), "+f"(d[51]), "+f"(d[52]), "+f"(d[53]), "+f"(d[54]), "+f"(d[55]), "+f"(d[56]), "+f"(d[57]), "+f"(d[58]), "+f"(d[59]), "+f"(d[60]), "+f"(d[61]), "+f"(d[62]), "+f"(d[63]), "+f"(d[64]), "+f"(d[65]), "+f"(d[66]), "+f"(d[67]), "+f"(d[68]), "+f"(d[69]), "+f"(d[70]), "+f"(d[71]), "+f"(d[72]), "+f"(d[73]), "+f"(d[74]), "+f"(d[75]), "+f"(d[76]), "+f"(d[77]), "+f"(d[78]), "+f"(d[79]), "+f"(d[80]), "+f"(d[81]), "+f"(d[82]), "+f"(d[83]), "+f"(d[84]), "+f"(d[85]), "+f"(d[86]), "+f"(d[87]), "+f"(d[88]), "+f"(d[89]), "+f"(d[90]), "+f"(d[91]), "+f"(d[92]), "+f"(d[93]), "+f"(d[94]), "+f"(d[95])
  : "l"(da), "l"(db), "r"(sd), "n"(TA), "n"(TB));
}
template<> struct WG<192> { template<int TA,int TB> static __device__ __forceinline__ void ss(float (&d)[96], uint64_t da, uint64_t db, int sd) { wgmma_ss_192<TA,TB>(d,da,db,sd); } };
template<int TA, int TB> __device__ __forceinline__ void wgmma_ss_160(float (&d)[80], uint64_t da, uint64_t db, int sd) {
  asm volatile("{\n.reg .pred p;\nsetp.ne.b32 p, %82, 0;\n"
  "wgmma.mma_async.sync.aligned.m64n160k16.f32.bf16.bf16 {%0, %1, %2, %3, %4, %5, %6, %7, %8, %9, %10, %11, %12, %13, %14, %15, %16, %17, %18, %19, %20, %21, %22, %23, %24, %25, %26, %27, %28, %29, %30, %31, %32, %33, %34, %35, %36, %37, %38, %39, %40, %41, %42, %43, %44, %45, %46, %47, %48, %49, %50, %51, %52, %53, %54, %55, %56, %57, %58, %59, %60, %61, %62, %63, %64, %65, %66, %67, %68, %69, %70, %71, %72, %73, %74, %75, %76, %77, %78, %79}, %80, %81, p, 1, 1, %83, %84;\n}\n"
  : "+f"(d[0]), "+f"(d[1]), "+f"(d[2]), "+f"(d[3]), "+f"(d[4]), "+f"(d[5]), "+f"(d[6]), "+f"(d[7]), "+f"(d[8]), "+f"(d[9]), "+f"(d[10]), "+f"(d[11]), "+f"(d[12]), "+f"(d[13]), "+f"(d[14]), "+f"(d[15]), "+f"(d[16]), "+f"(d[17]), "+f"(d[18]), "+f"(d[19]), "+f"(d[20]), "+f"(d[21]), "+f"(d[22]), "+f"(d[23]), "+f"(d[24]), "+f"(d[25]), "+f"(d[26]), "+f"(d[27]), "+f"(d[28]), "+f"(d[29]), "+f"(d[30]), "+f"(d[31]), "+f"(d[32]), "+f"(d[33]), "+f"(d[34]), "+f"(d[35]), "+f"(d[36]), "+f"(d[37]), "+f"(d[38]), "+f"(d[39]), "+f"(d[40]), "+f"(d[41]), "+f"(d[42]), "+f"(d[43]), "+f"(d[44]), "+f"(d[45]), "+f"(d[46]), "+f"(d[47]), "+f"(d[48]), "+f"(d[49]), "+f"(d[50]), "+f"(d[51]), "+f"(d[52]), "+f"(d[53]), "+f"(d[54]), "+f"(d[55]), "+f"(d[56]), "+f"(d[57]), "+f"(d[58]), "+f"(d[59]), "+f"(d[60]), "+f"(d[61]), "+f"(d[62]), "+f"(d[63]), "+f"(d[64]), "+f"(d[65]), "+f"(d[66]), "+f"(d[67]), "+f"(d[68]), "+f"(d[69]), "+f"(d[70]), "+f"(d[71]), "+f"(d[72]), "+f"(d[73]), "+f"(d[74]), "+f"(d[75]), "+f"(d[76]), "+f"(d[77]), "+f"(d[78]), "+f"(d[79])
  : "l"(da), "l"(db), "r"(sd), "n"(TA), "n"(TB));
}
template<> struct WG<160> { template<int TA,int TB> static __device__ __forceinline__ void ss(float (&d)[80], uint64_t da, uint64_t db, int sd) { wgmma_ss_160<TA,TB>(d,da,db,sd); } };

struct Params {
  const __nv_bfloat16 *x, *logA, *Aim, *Cre, *Cim, *logdt, *Dskip, *wg, *wu, *wd, *cvec, *wmod;
  __nv_bfloat16* out;
};

__device__ __forceinline__ void geglu_slice(uint32_t pg0, uint32_t pg1, uint32_t pu0, uint32_t pu1, uint32_t cpaddr,
                                            float r0, float m0, float r1, float m1, __nv_bfloat16* dst) {
  float4 cg = lds128f(cpaddr), cu = lds128f(cpaddr + 64);
  float g[4], u[4], o[4];
  g[0] = fmaf(bf_lo(pg0), r0, fmaf(m0, cg.x, cg.y)); g[1] = fmaf(bf_hi(pg0), r0, fmaf(m0, cg.z, cg.w));
  g[2] = fmaf(bf_lo(pg1), r1, fmaf(m1, cg.x, cg.y)); g[3] = fmaf(bf_hi(pg1), r1, fmaf(m1, cg.z, cg.w));
  u[0] = fmaf(bf_lo(pu0), r0, fmaf(m0, cu.x, cu.y)); u[1] = fmaf(bf_hi(pu0), r0, fmaf(m0, cu.z, cu.w));
  u[2] = fmaf(bf_lo(pu1), r1, fmaf(m1, cu.x, cu.y)); u[3] = fmaf(bf_hi(pu1), r1, fmaf(m1, cu.z, cu.w));
#pragma unroll
  for (int i = 0; i < 4; i++) {
    float t = tanhf_(g[i] * fmaf(g[i] * g[i], 0.7978845608f * 0.044715f, 0.7978845608f));
    float hh = 0.5f * g[i] * u[i];
    o[i] = fmaf(hh, t, hh);
  }
  *(uint32_t*)(dst) = pack_bf2(o[0], o[1]);
  *(uint32_t*)(dst + 64) = pack_bf2(o[2], o[3]);
}

template <int NSPLIT, int PART>
__device__ __forceinline__ void conv_finish(float (&acc)[16][4], uint32_t blk0, int bstep, uint32_t xaddr, float G, int lane, int barid) {
  constexpr int NT = 16 / NSPLIT;
  uint32_t mine = blk0 + PART * bstep + lane * 16;
#pragma unroll
  for (int j = 0; j < 16; j++) {
    if (j / NT != PART) {
      int jj = j < PART * NT ? j : j - NT;
      sts128f(mine + jj * 512, acc[j][0], acc[j][1], acc[j][2], acc[j][3]);
    }
  }
  nbar(barid, NSPLIT * 32);
#pragma unroll
  for (int o = 0; o < NSPLIT; o++) {
    if (o == PART) continue;
    uint32_t src = blk0 + o * bstep + lane * 16;
#pragma unroll
    for (int jl = 0; jl < NT; jl++) {
      int j = PART * NT + jl;
      int jj = j < o * NT ? j : j - NT;
      float4 v = lds128f(src + jj * 512);
      acc[j][0] += v.x; acc[j][1] += v.y; acc[j][2] += v.z; acc[j][3] += v.w;
    }
  }
#pragma unroll
  for (int jl = 0; jl < NT; jl += 2) {
    int j = PART * NT + jl;
    uint32_t a = xaddr + j * 128;
    uint32_t r0, r1, r2, r3;
    ldsm4t(a, r0, r1, r2, r3);
    r0 = pack_bf2(fmaf(G, acc[j][0], bf_lo(r0)), fmaf(G, acc[j][1], bf_hi(r0)));
    r1 = pack_bf2(fmaf(G, acc[j][2], bf_lo(r1)), fmaf(G, acc[j][3], bf_hi(r1)));
    r2 = pack_bf2(fmaf(G, acc[j + 1][0], bf_lo(r2)), fmaf(G, acc[j + 1][1], bf_hi(r2)));
    r3 = pack_bf2(fmaf(G, acc[j + 1][2], bf_lo(r3)), fmaf(G, acc[j + 1][3], bf_hi(r3)));
    stsm4t(a, r0, r1, r2, r3);
  }
}

__global__ void __cluster_dims__(2, 1, 1) __launch_bounds__(NTHR, 1)
fused_kernel(const Params P, const __grid_constant__ CUtensorMap tmX1, const __grid_constant__ CUtensorMap tmRes,
             const __grid_constant__ CUtensorMap tmWd) {
  extern __shared__ __align__(1024) unsigned char smem_raw[];
  const uint32_t sb = smem_u32(smem_raw);
  unsigned char* sp = smem_raw;
  if (sb & 1023u) __trap();
  const int tid = threadIdx.x, lane = tid & 31;
  const int warp = __shfl_sync(0xffffffffu, tid >> 5, 0);
  const int c = blockIdx.x;
  const int g = lane >> 2, q4 = lane & 3;
  const uint32_t bars = sb + SM_BARS;
  auto BAR = [&](int i) { return bars + 8 * i; };
  volatile unsigned* s_epoch = (volatile unsigned*)(sp + SM_BARS + 8 * 60);
  if (warp == 0) STAMP(0);

  uint4 ld[10];
  float cs_[10];
  const int ht = tid - 256;
  if (warp < 8) {
    const int row = tid >> 4;
    int t = 16 * (2 * (c & 63) + (row >> 3)) + 8 * (c >> 6) + (row & 7);
    const uint4* xr = (const uint4*)(P.x + t * DM);
#pragma unroll
    for (int k = 0; k < 5; k++) ld[k] = __ldg(xr + k * 16 + (tid & 15));
  } else {
#pragma unroll
    for (int it = 0; it < 10; it++) {
      int row = (ht >> 1) + 64 * it;
      ld[it] = make_uint4(0, 0, 0, 0);
      if (c < 120) ld[it] = __ldg((const uint4*)(P.wmod + row * 3840 + 16 * c + (ht & 1) * 8));
      cs_[it] = bfld(P.cvec + row);
    }
  }
  const int ch = warp < 8 ? (warp & 3) : 4;
  const int part = warp < 8 ? (warp >> 2) : (warp & 3);
  const int nsplit = warp < 8 ? 2 : 4;
  const int dch = 5 * c + ch;
  float pla[2], pai[2], pcr[2], pci[2], pdt = 0.f, pD = 0.f; uint2 call_r = make_uint2(0, 0), call_i = make_uint2(0, 0);
  {
#pragma unroll
    for (int i = 0; i < 2; i++) {
      int n = dch * 128 + part * (128 / nsplit) + (i * 32 + lane) % (128 / nsplit);
      pla[i] = bfld(P.logA + n); pai[i] = bfld(P.Aim + n); pcr[i] = bfld(P.Cre + n); pci[i] = bfld(P.Cim + n);
    }
    call_r = __ldg((const uint2*)(P.Cre + dch * 128) + lane);
    call_i = __ldg((const uint2*)(P.Cim + dch * 128) + lane);
    pdt = bfld(P.logdt + dch); pD = bfld(P.Dskip + dch);
  }
  if (tid == 0) {
    mbar_init(BAR(B_DATA), 1);
    for (int i = 0; i < 10; i++) { mbar_init(BAR(B_FULLA + i), 1); mbar_init(BAR(B_FREEA + i), 2); }
    for (int i = 0; i < 4; i++) { mbar_init(BAR(B_FULLB + i), 1); mbar_init(BAR(B_EMPTYB + i), 2); }
    for (int i = 0; i < 8; i++) { mbar_init(BAR(B_FULL2 + i), 1); mbar_init(BAR(B_EMPTY2 + i), 2); }
    mbar_init(BAR(B_STATS), 32); mbar_init(BAR(B_CP), 1); mbar_init(BAR(B_HA), 8); mbar_init(BAR(B_HB), 8);
    mbar_init(BAR(B_RES), 1); mbar_init(BAR(B_XRDY), 1); mbar_init(BAR(B_XFULL), 1);
    asm volatile("fence.mbarrier_init.release.cluster;" ::: "memory");
    fence_async_smem();
  }
  asm volatile("barrier.cluster.arrive.release.aligned;" ::: "memory");

  float* s_red = (float*)(sp + SM_RED);
  auto gemv16 = [&](int col0) {
    float a[8];
#pragma unroll
    for (int i = 0; i < 8; i++) a[i] = 0.f;
#pragma unroll
    for (int it = 0; it < 10; it++) {
      const float s = cs_[it];
      a[0] = fmaf(s, bf_lo(ld[it].x), a[0]); a[1] = fmaf(s, bf_hi(ld[it].x), a[1]);
      a[2] = fmaf(s, bf_lo(ld[it].y), a[2]); a[3] = fmaf(s, bf_hi(ld[it].y), a[3]);
      a[4] = fmaf(s, bf_lo(ld[it].z), a[4]); a[5] = fmaf(s, bf_hi(ld[it].z), a[5]);
      a[6] = fmaf(s, bf_lo(ld[it].w), a[6]); a[7] = fmaf(s, bf_hi(ld[it].w), a[7]);
    }
#pragma unroll
    for (int o = 2; o < 32; o <<= 1)
#pragma unroll
      for (int i = 0; i < 8; i++) a[i] += __shfl_xor_sync(0xffffffffu, a[i], o);
    if (lane < 2) {
#pragma unroll
      for (int i = 0; i < 8; i++) s_red[(warp - 8) * 16 + lane * 8 + i] = a[i];
    }
    nbar(7, 128);
    if (ht < 16 && c < 120) g_mod[col0 + ht] = bf16r(s_red[ht] + s_red[16 + ht] + s_red[32 + ht] + s_red[48 + ht]);
    nbar(7, 128);
  };
  if (warp < 8) {
    float f[40];
#pragma unroll
    for (int k = 0; k < 5; k++) {
      f[8 * k] = bf_lo(ld[k].x); f[8 * k + 1] = bf_hi(ld[k].x); f[8 * k + 2] = bf_lo(ld[k].y); f[8 * k + 3] = bf_hi(ld[k].y);
      f[8 * k + 4] = bf_lo(ld[k].z); f[8 * k + 5] = bf_hi(ld[k].z); f[8 * k + 6] = bf_lo(ld[k].w); f[8 * k + 7] = bf_hi(ld[k].w);
    }
    float s = 0.f;
#pragma unroll
    for (int i = 0; i < 40; i++) s += f[i];
#pragma unroll
    for (int o = 8; o; o >>= 1) s += __shfl_xor_sync(0xffffffffu, s, o);
    float mean = s * (1.0f / DM), q = 0.f;
#pragma unroll
    for (int i = 0; i < 40; i++) { f[i] -= mean; q = fmaf(f[i], f[i], q); }
#pragma unroll
    for (int o = 8; o; o >>= 1) q += __shfl_xor_sync(0xffffffffu, q, o);
    float r = rsqrtf(q * (1.0f / DM) + 1e-5f);
    const int row = tid >> 4;
    int rho = ((row >> 1) & 1) * 8 + (row >> 2) * 2 + (row & 1);
#pragma unroll
    for (int k = 0; k < 5; k++) {
      sts128(sb + SM_XS + rho * XROW + (k * 16 + (tid & 15)) * 16, ld[k]);
      sts128(sb + SM_VS + rho * XROW + (k * 16 + (tid & 15)) * 16,
             make_uint4(pack_h2(f[8 * k] * r, f[8 * k + 1] * r), pack_h2(f[8 * k + 2] * r, f[8 * k + 3] * r),
                        pack_h2(f[8 * k + 4] * r, f[8 * k + 5] * r), pack_h2(f[8 * k + 6] * r, f[8 * k + 7] * r)));
    }
  } else {
#pragma unroll
    for (int it = 0; it < 10; it++) cs_[it] = bf16r(cs_[it] / (1.0f + __expf(-cs_[it])));
    gemv16(16 * c);
  }
  __syncthreads();
#pragma unroll 1
  for (int job = warp; job < 80; job += 12) {
    int arr = job >= 40, gp = job - 40 * arr;
    uint32_t a = sb + (arr ? SM_VS : SM_XS) + (((lane >> 3) & 1) * 8 + (lane & 7)) * XROW + (16 * gp + 8 * (lane >> 4)) * 2;
    uint32_t r0, r1, r2, r3;
    ldsm4t(a, r0, r1, r2, r3);
    unsigned short* dst = (arr ? (unsigned short*)g_vT : (unsigned short*)g_xT) + (16 * gp + g) * LSEQ + 16 * c + 4 * q4;
    *(uint2*)dst = make_uint2(r0, r1);
    *(uint2*)(dst + 8 * LSEQ) = make_uint2(r2, r3);
  }
  asm volatile("barrier.cluster.wait.acquire.aligned;" ::: "memory");
  __syncthreads();
  if (warp == 0) STAMP(1);
  const __nv_bfloat16* wsrc = ((c >= 54) ? P.wu : P.wg) + 32 * (c >= 54 ? c - 54 : c);
  unsigned ep = 0;
  if (warp >= 8) {
    if (ht == 0) {
      unsigned old;
      asm volatile("atom.add.release.gpu.global.u32 %0, [%1], 1;" : "=r"(old) : "l"(&g_cnt[C_BAR1 * 32]) : "memory");
      *s_epoch = (old >> 7) + 1;
      asm volatile("cp.async.bulk.prefetch.L2.global [%0], %1;" ::"l"((const char*)P.wd + c * 17280), "r"(17280) : "memory");
    }
#pragma unroll
    for (int it = 0; it < 10; it++) {
      int row = (ht >> 1) + 64 * it;
      if (c < 120) ld[it] = __ldg((const uint4*)(P.wmod + row * 3840 + 1920 + 16 * c + (ht & 1) * 8));
    }
    if (c < 108) {
#pragma unroll
      for (int r = 0; r < 5; r++) asm volatile("prefetch.global.L2 [%0];" ::"l"(wsrc + (ht + 128 * r) * DF));
    }
  }

  const int kh = c & 1, n4 = (c >> 1) & 3, mt = c >> 3, jj = 4 * kh + n4;

  {
    const int gsz = nsplit * 32, gtid = part * 32 + lane, barid = 1 + ch;
    const int bstep = warp < 8 ? 4 * 4672 : 6144, blk0 = wblk(warp < 8 ? ch : 8);
    float dt = bf16r(expf(pdt));
    float scC = fmaxf(fmaxf(fmaxf(fabsf(bf_lo(call_r.x)), fabsf(bf_hi(call_r.x))), fmaxf(fabsf(bf_lo(call_r.y)), fabsf(bf_hi(call_r.y)))),
                      fmaxf(fmaxf(fabsf(bf_lo(call_i.x)), fabsf(bf_hi(call_i.x))), fmaxf(fabsf(bf_lo(call_i.y)), fabsf(bf_hi(call_i.y)))));
#pragma unroll
    for (int o = 16; o; o >>= 1) scC = fmaxf(scC, __shfl_xor_sync(0xffffffffu, scC, o));
    scC = fmaxf(scC, 1e-30f);
    const float iscC = 1.0f / scC;
    const uint32_t tab = sb + wblk(warp);
    float k2048 = 0.f;
#pragma unroll
    for (int i = 0; i < 2; i++) {
      if (i * 32 < 128 / nsplit) {
        float lr2 = -bf16r(expf(pla[i])) * dt * 1.4426950408889634f;
        float th = pai[i] * dt * 0.15915494309189535f; th -= rintf(th);
        cf C; C.r = pcr[i] * iscC; C.i = pci[i] * iscC;
        cf z8 = cpow_direct(lr2, th, 8.f), z128 = cpow_direct(lr2, th, 128.f), z2k = cpow_direct(lr2, th, 2048.f);
        k2048 += C.r * z2k.r - C.i * z2k.i;
        uint32_t a = tab + (i * 32 + lane) * 32;
        sts128f(a, lr2, th * 6.283185307179586f, C.r, C.i);
        sts128f(a + 16, z8.r, z8.i, z128.r, z128.i);
      }
    }
#pragma unroll
    for (int o = 16; o; o >>= 1) k2048 += __shfl_xor_sync(0xffffffffu, k2048, o);
    __syncwarp();
    float T[5][4];
#pragma unroll
    for (int s = 0; s < 5; s++) { T[s][0] = T[s][1] = T[s][2] = T[s][3] = 0.f; }
    const float gf = (float)g;
    const int nks = 16 / nsplit;
#pragma unroll 1
    for (int ks = 0; ks < nks; ks++) {
      uint32_t A[4][4], B[5][2];
#pragma unroll
      for (int h = 0; h < 2; h++) {
        uint32_t a = tab + (ks * 8 + q4 + 4 * h) * 32;
        float4 s0 = lds128f(a), s1 = lds128f(a + 16);
        float m = ex2f(s0.x * gf), an = s0.y * gf;
        cf u; u.r = m * __cosf(an); u.i = m * __sinf(an);
        cf z8; z8.r = s1.x; z8.i = s1.y; cf z128; z128.r = s1.z; z128.i = s1.w; cf C; C.r = s0.z; C.i = s0.w;
        cf u2 = cmul(u, z8);
        A[0][2 * h] = pack_h2(u.r, u.i); A[0][2 * h + 1] = pack_h2(u2.r, u2.i);
#pragma unroll
        for (int k = 1; k < 4; k++) { u = csq(u); u2 = csq(u2); A[k][2 * h] = pack_h2(u.r, u.i); A[k][2 * h + 1] = pack_h2(u2.r, u2.i); }
        cf w = csq(u);
        cf b = cmul(C, w); B[0][h] = pack_h2(b.r, -b.i);
        b = cmul(b, z128); B[1][h] = pack_h2(b.r, -b.i);
        w = cmul(w, z128);
        b = cmul(b, w); B[2][h] = pack_h2(b.r, -b.i);
        w = csq(w);
        b = cmul(b, w); B[3][h] = pack_h2(b.r, -b.i);
        w = csq(w);
        b = cmul(b, w); B[4][h] = pack_h2(b.r, -b.i);
      }
      mma_f16(T[0], A[0][0], A[0][1], A[0][2], A[0][3], B[0][0], B[0][1]);
      mma_f16(T[1], A[0][0], A[0][1], A[0][2], A[0][3], B[1][0], B[1][1]);
      mma_f16(T[2], A[1][0], A[1][1], A[1][2], A[1][3], B[2][0], B[2][1]);
      mma_f16(T[3], A[2][0], A[2][1], A[2][2], A[2][3], B[3][0], B[3][1]);
      mma_f16(T[4], A[3][0], A[3][1], A[3][2], A[3][3], B[4][0], B[4][1]);
    }
    {
      float* kp = (float*)(sp + wblk(warp) + 2048);
#pragma unroll
      for (int s = 0; s < 5; s++) {
        kp[128 * s + 32 * q4 + g] = T[s][0]; kp[128 * s + 32 * q4 + 16 + g] = T[s][1];
        kp[128 * s + 32 * q4 + g + 8] = T[s][2]; kp[128 * s + 32 * q4 + 24 + g] = T[s][3];
      }
      if (lane == 0) kp[640] = k2048;
    }
    if (warp == 0) STAMP(2);
    nbar(barid, gsz);
    const float cK0 = 2.0f * dt * scC;
    const float sK = fmaxf(fmaxf(cK0, fabsf(pD)), 1e-30f);
    {
      const float cK = cK0 / sK, dK = pD / sK;
      const float* kp = (const float*)(sp + blk0 + 2048);
      __half* kh_ = (__half*)(sp + SM_KH + ch * 1296);
      for (int i = gtid; i < 641; i += gsz) {
        float s = 0.f;
        for (int o = 0; o < nsplit; o++) s += kp[o * (bstep / 4) + i];
        s *= cK; if (i == 0) s += dK;
        kh_[i] = __float2half_rn(s);
      }
    }
    nbar(barid, gsz);
    {
      const unsigned short* kh_ = (const unsigned short*)(sp + SM_KH + ch * 1296);
      uint32_t* pt = (uint32_t*)(sp + SM_PT) + ch * PTW;
      for (int i = gtid; i < PTW; i += gsz) {
        int x = i - 16;
        uint32_t lo = (x >= 0 && x < LSEQ) ? kh_[krank(x)] : 0u;
        uint32_t hi = (x >= 1 && x <= LSEQ) ? kh_[krank(x - 1)] : 0u;
        pt[i] = lo | (hi << 16);
      }
      if (gtid < 16) sts128(sb + SM_H + ch * 2 * HPL + (gtid >> 3) * HPL + (gtid & 7) * 16, make_uint4(0, 0, 0, 0));
    }
    if (warp == 0) STAMP(3);
    if (warp >= 8) {
      ep = *s_epoch;
      if (ht == 0) {
        poll_ge(&g_cnt[C_BAR1 * 32], ep * 128);
        fence_async();
        STAMP(16);
        mbar_expect_tx(BAR(B_DATA), 5 * 8192);
#pragma unroll 1
        for (int k = 0; k < 5; k++) {
          const __half* v = g_vT + (5 * c + k) * LSEQ;
          bulk_g2s(sb + SM_H + k * 2 * HPL + 128, v, 2048, BAR(B_DATA));
          bulk_g2s(sb + SM_H + k * 2 * HPL + HPL + 128, v + 1024, 2048, BAR(B_DATA));
          bulk_g2s(sb + SM_X + k * 4096, g_xT + (5 * c + k) * LSEQ, 4096, BAR(B_DATA));
        }
      }
      __syncwarp();
      gemv16(1920 + 16 * c);
      if (ht == 0) red_release(&g_cnt[C_MOD2 * 32], 1);
      if (lane == 0) poll_ge(&g_cnt[C_MOD2 * 32], ep * 128);
      __syncwarp();
      if (warp == 8) STAMP(17);
      if (c < 108) {
        const int hw = warp - 8;
        const int up = c >= 54;
        const int f = 32 * (up ? c - 54 : c) + 8 * (lane & 3);
        const int fh = f >= 864, fl = f - 864 * fh;
        const int pb = fl >= 4 * FA;
        const int fn = pb ? (fl - 4 * FA) / FB : fl / FA;
        const int tile = (pb ? (fl - 4 * FA) - fn * FB : fl - fn * FA) >> 3;
        const int j8 = 4 * fh + fn;
        const int nt = pb ? NB / 8 : NA / 8;
        __nv_bfloat16* dst = g_Wp + j8 * (BLOB_A + BLOB_B) + (pb ? BLOB_A : 0) + (2 * tile + up) * 64 + (lane >> 2) * 8;
        float cs[8], sw[8];
#pragma unroll
        for (int i = 0; i < 8; i++) { cs[i] = 0.f; sw[i] = 0.f; }
#pragma unroll 10
        for (int it = 0; it < 20; it++) {
          int rg = hw + 4 * it;
          int d = 8 * rg + (lane >> 2);
          uint4 w = __ldg((const uint4*)(wsrc + d * DF + 8 * (lane & 3)));
          float sbv = ldg_relaxed(g_mod + 3 * DM + d), cb1 = bf16r(1.0f + ldg_relaxed(g_mod + 4 * DM + d));
          float e[8] = {bf_lo(w.x), bf_hi(w.x), bf_lo(w.y), bf_hi(w.y), bf_lo(w.z), bf_hi(w.z), bf_lo(w.w), bf_hi(w.w)};
#pragma unroll
          for (int i = 0; i < 8; i++) { sw[i] = fmaf(sbv, e[i], sw[i]); e[i] *= cb1; }
          uint4 o = make_uint4(pack_bf2(e[0], e[1]), pack_bf2(e[2], e[3]), pack_bf2(e[4], e[5]), pack_bf2(e[6], e[7]));
          cs[0] += bf_lo(o.x); cs[1] += bf_hi(o.x); cs[2] += bf_lo(o.y); cs[3] += bf_hi(o.y);
          cs[4] += bf_lo(o.z); cs[5] += bf_hi(o.z); cs[6] += bf_lo(o.w); cs[7] += bf_hi(o.w);
          *(uint4*)(dst + rg * nt * 64) = o;
        }
#pragma unroll
        for (int o = 4; o < 32; o <<= 1)
#pragma unroll
          for (int i = 0; i < 8; i++) { cs[i] += __shfl_xor_sync(0xffffffffu, cs[i], o); sw[i] += __shfl_xor_sync(0xffffffffu, sw[i], o); }
        if (lane < 4) {
#pragma unroll
          for (int i = 0; i < 8; i++) { s_red[hw * 64 + lane * 16 + 2 * i] = cs[i]; s_red[hw * 64 + lane * 16 + 2 * i + 1] = sw[i]; }
        }
        nbar(7, 128);
        if (hw == 0) {
          int idx = j8 * (NA + NB) + (pb ? NA : 0) + (2 * tile + up) * 8;
          idx = __shfl_sync(0xffffffffu, idx, lane >> 3) + (lane & 7);
          float2 v;
          v.x = s_red[2 * lane] + s_red[64 + 2 * lane] + s_red[128 + 2 * lane] + s_red[192 + 2 * lane];
          v.y = s_red[2 * lane + 1] + s_red[65 + 2 * lane] + s_red[129 + 2 * lane] + s_red[193 + 2 * lane];
          g_cp[idx] = v;
        }
      }
      if (warp == 8) STAMP(18);
    }
    mbar_wait(BAR(B_DATA), 0);
    if (warp == 0) STAMP(4);
    float G;
    {
      float sa = ldg_relaxed(g_mod + dch), ca1 = bf16r(1.0f + ldg_relaxed(g_mod + DM + dch)), ga = ldg_relaxed(g_mod + 2 * DM + dch);
      float mx = fmaxf(fmaxf(fabsf(sa), fabsf(ca1)), 1e-30f);
      float sh = __uint_as_float((__float_as_uint(mx) & 0x7f800000u) + 0x00800000u);
      float ish = 1.0f / sh;
      G = ga * sh * sK;
      __half2 ha = __float2half2_rn(ca1 * ish), hb = __float2half2_rn(sa * ish);
      for (int u = gtid; u < 256; u += gsz) {
        uint32_t a = sb + SM_H + ch * 2 * HPL + (u >> 7) * HPL + 128 + (u & 127) * 16;
        uint4 v = lds128(a);
        __half2 t;
        t = __hfma2(*(__half2*)&v.x, ha, hb); v.x = *(uint32_t*)&t;
        t = __hfma2(*(__half2*)&v.y, ha, hb); v.y = *(uint32_t*)&t;
        t = __hfma2(*(__half2*)&v.z, ha, hb); v.z = *(uint32_t*)&t;
        t = __hfma2(*(__half2*)&v.w, ha, hb); v.w = *(uint32_t*)&t;
        sts128(a, v);
      }
    }
    nbar(barid, gsz);
    float acc[16][4];
#pragma unroll
    for (int j = 0; j < 16; j++) { acc[j][0] = acc[j][1] = acc[j][2] = acc[j][3] = 0.f; }
    const uint32_t hbase = sb + SM_H + ch * 2 * HPL + ((lane >> 3) & 1) * HPL + 128 + ((lane >> 4) * 8 + (lane & 7)) * 16;
    const uint32_t ptb = sb + SM_PT + ch * PTW * 4 + (16 + g - 2 * q4) * 4;
#pragma unroll 1
    for (int s0 = part; s0 < 8; s0 += nsplit) {
      uint32_t Bf[16][2];
#pragma unroll
      for (int j = 0; j < 16; j += 2) ldsm4(hbase + j * 128 - s0 * 16, Bf[j][0], Bf[j][1], Bf[j + 1][0], Bf[j + 1][1]);
      const uint32_t pa = ptb + s0 * 64;
#pragma unroll
      for (int s1 = 0; s1 < 16; s1++) {
        uint32_t a0 = lds32(pa + s1 * 512), a1 = lds32(pa + s1 * 512 + 32), a2 = lds32(pa + s1 * 512 - 32);
#pragma unroll
        for (int j = s1; j < 16; j++) mma_f16(acc[j], a0, a1, a2, a0, Bf[j - s1][0], Bf[j - s1][1]);
      }
    }
    if (warp == 0) STAMP(5);
    const uint32_t xaddr = sb + SM_X + ch * 4096 + ((lane >> 3) & 1) * 2048 + ((lane >> 4) * 8 + (lane & 7)) * 16;
    if (nsplit == 2) {
      if (part == 0) conv_finish<2, 0>(acc, sb + blk0, bstep, xaddr, G, lane, barid);
      else conv_finish<2, 1>(acc, sb + blk0, bstep, xaddr, G, lane, barid);
    } else {
      if (part == 0) conv_finish<4, 0>(acc, sb + blk0, bstep, xaddr, G, lane, barid);
      else if (part == 1) conv_finish<4, 1>(acc, sb + blk0, bstep, xaddr, G, lane, barid);
      else if (part == 2) conv_finish<4, 2>(acc, sb + blk0, bstep, xaddr, G, lane, barid);
      else conv_finish<4, 3>(acc, sb + blk0, bstep, xaddr, G, lane, barid);
    }
    fence_async_smem();
    nbar(barid, gsz);
    if (gtid == 0) {
      bulk_s2g(g_x1T + dch * LSEQ, sb + SM_X + ch * 4096, 4096);
      asm volatile("cp.async.bulk.commit_group;" ::: "memory");
      asm volatile("cp.async.bulk.wait_group 0;" ::: "memory");
      fence_async();
      red_release(&g_cnt[C_BAR2 * 32], 1);
    }
    if (warp == 0) STAMP(6);
  }

  const int wgi = warp >> 2;
  if (wgi < 2) {
    asm volatile("setmaxnreg.inc.sync.aligned.u32 232;");
    const bool elect = (tid & 127) == 0;
    const uint64_t dA = mkdesc(sb + SM_A + wgi * 8192, 1024, 1024, 1);
    uint32_t pk[NA / 4];
    {
      float acc[NA / 2];
      const uint64_t dB = mkdesc(sb + SM_B, (NA / 8) * 128, 128, 0);
#pragma unroll 4
      for (int ks = 0; ks < 20; ks++) {
        const int s = ks & 3;
        if ((ks & 1) == 0) mbar_wait(BAR(B_FULLA + (ks >> 1)), 0);
        mbar_wait(BAR(B_FULLB + s), (ks >> 2) & 1);
        if (ks == 0 && warp == 0) STAMP(8);
        wg_fence();
        const uint64_t a = dA + (uint32_t)((ks >> 1) * 1024 + (ks & 1) * 256), b = dB + (uint32_t)(s * (BST >> 4));
        WG<NA>::ss<1, 1>(acc, a, b, ks > 0);
        WG<NA>::ss<1, 1>(acc, a + 128, b + (NA / 8) * 16, 1);
        wg_commit();
        wg_wait<1>();
        if (ks > 0 && elect) mbar_arrive(BAR(B_EMPTYB + ((ks - 1) & 3)));
      }
      wg_wait<0>();
      if (elect) mbar_arrive(BAR(B_EMPTYB + 3));
#pragma unroll
      for (int i = 0; i < NA / 4; i++) pk[i] = pack_bf2(acc[2 * i], acc[2 * i + 1]);
    }
    if (warp == 0) STAMP(9);
    const int wrow = wgi * 64 + (warp & 3) * 16;
    float r0, m0, r1, m1;
    const uint32_t cpa = sb + SM_CP + q4 * 16;
    __nv_bfloat16* hdst = g_h + (mt * 216 + 108 * kh) * 1024 + (wrow >> 3) * 64 + lane * 2;
    uint32_t pk2[NB / 4];
    {
      float acc[NB / 2];
      const uint64_t dB = mkdesc(sb + SM_B, (NB / 8) * 128, 128, 0);
#pragma unroll
      for (int ks = 0; ks < 20; ks++) {
        const int s = ks & 3;
        mbar_wait(BAR(B_FULLB + s), ((20 + ks) >> 2) & 1);
        wg_fence();
        const uint64_t a = dA + (uint32_t)((ks >> 1) * 1024 + (ks & 1) * 256), b = dB + (uint32_t)(s * (BST >> 4));
        WG<NB>::ss<1, 1>(acc, a, b, ks > 0);
        WG<NB>::ss<1, 1>(acc, a + 128, b + (NB / 8) * 16, 1);
        wg_commit();
        if (ks == 0) {
          mbar_wait(BAR(B_STATS), 0); mbar_wait(BAR(B_CP), 0);
          float2 t0 = *(const float2*)(sp + SM_ST2 + (wrow + g) * 8), t1 = *(const float2*)(sp + SM_ST2 + (wrow + g + 8) * 8);
          r0 = t0.x; m0 = t0.y; r1 = t1.x; m1 = t1.y;
        }
        if (ks < TA_) geglu_slice(pk[4 * ks], pk[4 * ks + 1], pk[4 * ks + 2], pk[4 * ks + 3], cpa + ks * 128, r0, m0, r1, m1,
                                  hdst + (n4 * TA_ + ks) * 1024);
        if (ks == TA_ - 1) { __syncwarp(); if (lane == 0) mbar_arrive(BAR(B_HA)); }
        wg_wait<1>();
        if (ks > 0 && elect) {
          mbar_arrive(BAR(B_EMPTYB + ((ks - 1) & 3)));
          if ((ks & 1) == 0) mbar_arrive(BAR(B_FREEA + (ks >> 1) - 1));
        }
      }
      wg_wait<0>();
      if (elect) mbar_arrive(BAR(B_FREEA + 9));
#pragma unroll
      for (int i = 0; i < NB / 4; i++) pk2[i] = pack_bf2(acc[2 * i], acc[2 * i + 1]);
    }
    if (warp == 0) STAMP(10);
    float acc[80];
    {
      const uint64_t dH = mkdesc(sb + wgi * 1024, 2048, 128, 0);
      const uint64_t dW = mkdesc(sb + 8192, 2048, 512, 2);
#pragma unroll
      for (int s2 = 0; s2 < 8; s2++) {
        mbar_wait(BAR(B_FULL2 + s2), 0);
        wg_fence();
        const uint64_t a = dH + (uint32_t)(s2 * (SLOT2 >> 4)), b = dW + (uint32_t)(s2 * (SLOT2 >> 4));
        WG<160>::ss<0, 1>(acc, a, b, s2 > 0);
        WG<160>::ss<0, 1>(acc, a + 256, b + 64, 1);
        wg_commit();
#pragma unroll
        for (int i = 2 * s2; i < 2 * s2 + 2; i++)
          if (i < TB_) geglu_slice(pk2[4 * i], pk2[4 * i + 1], pk2[4 * i + 2], pk2[4 * i + 3], cpa + NA * 8 + i * 128, r0, m0, r1, m1,
                                   hdst + (4 * TA_ + n4 * TB_ + i) * 1024);
        if (2 * s2 + 2 >= TB_ && 2 * s2 < TB_) { __syncwarp(); if (lane == 0) mbar_arrive(BAR(B_HB)); }
        wg_wait<1>();
        if (s2 > 0 && elect) mbar_arrive(BAR(B_EMPTY2 + s2 - 1));
      }
#pragma unroll 1
      for (int s2 = 8; s2 < S2; s2++) {
        const int s = s2 & 7;
        mbar_wait(BAR(B_FULL2 + s), (s2 >> 3) & 1);
        wg_fence();
        const uint64_t a = dH + (uint32_t)(s * (SLOT2 >> 4)), b = dW + (uint32_t)(s * (SLOT2 >> 4));
        WG<160>::ss<0, 1>(acc, a, b, 1);
        WG<160>::ss<0, 1>(acc, a + 256, b + 64, 1);
        wg_commit();
        wg_wait<1>();
        if (elect) mbar_arrive(BAR(B_EMPTY2 + ((s2 - 1) & 7)));
      }
      wg_wait<0>();
    }
    if (warp == 0) STAMP(11);
    const int ct = tid;
    const uint32_t xch = sb + SM_XCH + (ct >> 5) * 5120 + lane * 16;
    mbar_wait_cluster(BAR(B_XRDY), 0);
    {
      const uint32_t rdst = mapa(xch, kh ^ 1), rbar = mapa(BAR(B_XFULL), kh ^ 1);
#pragma unroll
      for (int i = 0; i < 10; i++) {
        float v0 = kh ? acc[4 * i] : acc[40 + 4 * i], v1 = kh ? acc[4 * i + 1] : acc[41 + 4 * i];
        float v2 = kh ? acc[4 * i + 2] : acc[42 + 4 * i], v3 = kh ? acc[4 * i + 3] : acc[43 + 4 * i];
        asm volatile("st.async.weak.shared::cluster.mbarrier::complete_tx::bytes.v4.f32 [%0], {%1,%2,%3,%4}, [%5];"
                     ::"r"(rdst + i * 512), "f"(v0), "f"(v1), "f"(v2), "f"(v3), "r"(rbar) : "memory");
      }
    }
    const int col0 = 160 * n4 + 80 * kh;
    float2 gbv[10];
#pragma unroll
    for (int i = 0; i < 10; i++) {
      gbv[i].x = ldg_relaxed(g_mod + 5 * DM + col0 + 8 * i + 2 * q4);
      gbv[i].y = ldg_relaxed(g_mod + 5 * DM + col0 + 8 * i + 2 * q4 + 1);
    }
    mbar_wait(BAR(B_RES), 0);
    uint32_t xr[20];
    {
      const int mi = lane >> 3, rr = lane & 7;
      const int chunk = (warp & 3) * 2 + (mi & 1);
      const uint32_t a = sb + SM_RES + wgi * 10240 + ((mi >> 1) * 8 + rr) * 128 + ((chunk ^ rr) << 4);
#pragma unroll
      for (int i = 0; i < 10; i += 2) ldsm4t(a + i * 1024, xr[2 * i], xr[2 * i + 1], xr[2 * i + 2], xr[2 * i + 3]);
    }
    mbar_wait_cluster(BAR(B_XFULL), 0);
    uint32_t ow[20];
#pragma unroll
    for (int i = 0; i < 10; i++) {
      float4 v = lds128f(xch + i * 512);
      float a0 = (kh ? acc[40 + 4 * i] : acc[4 * i]) + v.x, a1 = (kh ? acc[41 + 4 * i] : acc[4 * i + 1]) + v.y;
      float a2 = (kh ? acc[42 + 4 * i] : acc[4 * i + 2]) + v.z, a3 = (kh ? acc[43 + 4 * i] : acc[4 * i + 3]) + v.w;
      ow[2 * i] = pack_bf2(fmaf(gbv[i].x, a0, bf_lo(xr[2 * i])), fmaf(gbv[i].y, a1, bf_hi(xr[2 * i])));
      ow[2 * i + 1] = pack_bf2(fmaf(gbv[i].x, a2, bf_lo(xr[2 * i + 1])), fmaf(gbv[i].y, a3, bf_hi(xr[2 * i + 1])));
    }
    __syncwarp();
    const uint32_t stg = sb + SM_XCH + (ct >> 5) * 5120;
    {
      const int mi = lane >> 3, rr = lane & 7;
      const uint32_t a = stg + ((mi & 1) * 8 + rr) * 176 + (mi >> 1) * 16;
#pragma unroll
      for (int i = 0; i < 10; i += 2) stsm4(a + i * 16, ow[2 * i], ow[2 * i + 1], ow[2 * i + 2], ow[2 * i + 3]);
    }
    __syncwarp();
#pragma unroll
    for (int i = 0; i < 5; i++) {
      int u = i * 32 + lane, row = u / 10, cu = u - row * 10;
      uint4 v = lds128(stg + row * 176 + cu * 16);
      int mrow = (warp & 3) * 16 + row;
      int t = 128 * mt + 16 * (mrow >> 3) + 8 * wgi + (mrow & 7);
      *(uint4*)(P.out + t * DM + col0 + cu * 8) = v;
    }
    if (warp == 0) STAMP(12);
  } else {
    asm volatile("setmaxnreg.dec.sync.aligned.u32 40;");
    if (warp == 8) {
      if (lane == 0) {
        poll_ge(&g_cnt[C_BAR2 * 32], ep * 640);
        fence_async();
        STAMP(19);
        const __nv_bfloat16* blob = g_Wp + jj * (BLOB_A + BLOB_B);
#pragma unroll 1
        for (int k = 0; k < 10; k++) {
          if (k < 4) { mbar_expect_tx(BAR(B_FULLB + k), BST); bulk_g2s(sb + SM_B + k * BST, blob + k * 32 * NA, BST, BAR(B_FULLB + k)); }
          mbar_expect_tx(BAR(B_FULLA + k), 16384);
          tma2d(sb + SM_A + k * 16384, &tmX1, 64 * mt, 64 * k, BAR(B_FULLA + k));
          tma2d(sb + SM_A + k * 16384 + 8192, &tmX1, 1024 + 64 * mt, 64 * k, BAR(B_FULLA + k));
        }
        mbar_expect_tx(BAR(B_CP), (NA + NB) * 8);
        bulk_g2s(sb + SM_CP, g_cp + jj * (NA + NB), (NA + NB) * 8, BAR(B_CP));
#pragma unroll 1
        for (int kb = 4; kb < 40; kb++) {
          const int s = kb & 3;
          mbar_wait(BAR(B_EMPTYB + s), ((kb >> 2) & 1) ^ 1);
          const uint32_t bytes = kb < 20 ? BST : 32 * NB * 2;
          const __nv_bfloat16* src = kb < 20 ? blob + kb * 32 * NA : blob + BLOB_A + (kb - 20) * 32 * NB;
          mbar_expect_tx(BAR(B_FULLB + s), bytes);
          bulk_g2s(sb + SM_B + s * BST, src, bytes, BAR(B_FULLB + s));
        }
      }
    } else if (warp == 9) {
      if (lane == 0) poll_ge(&g_cnt[(C_ST + mt) * 32], ep * 8);
      __syncwarp();
      {
        const float* src = (const float*)g_st2 + mt * 256 + lane * 8;
        float* dst = (float*)(sp + SM_ST2) + lane * 8;
#pragma unroll
        for (int i = 0; i < 8; i++) dst[i] = ldg_relaxed(src + i);
      }
      mbar_arrive(BAR(B_STATS));
      if (lane == 0) {
        mbar_wait(BAR(B_HA), 0);
        __threadfence();
        red_release(&g_cnt[(C_HA + 2 * mt + kh) * 32], 1);
        mbar_wait(BAR(B_HB), 0);
        __threadfence();
        red_release(&g_cnt[(C_HB + 2 * mt + kh) * 32], 1);
      }
    } else if (warp == 10) {
      if (lane == 0) {
        mbar_expect_tx(BAR(B_XFULL), 40960);
        const __nv_bfloat16* hsrc = g_h + (mt * 216 + 108 * kh) * 1024;
#pragma unroll 1
        for (int s2 = 0; s2 < S2; s2++) {
          const int s = s2 & 7;
          if (s2 < 8) mbar_wait(BAR(B_FREEA + s2 + 1), 0);
          else mbar_wait(BAR(B_EMPTY2 + s), ((s2 >> 3) & 1) ^ 1);
          mbar_expect_tx(BAR(B_FULL2 + s), SLOT2);
          tma3d(sb + s * SLOT2 + 8192, &tmWd, 0, 864 * kh + 32 * s2, 5 * n4, BAR(B_FULL2 + s));
          if (s2 == 0) { poll_ge(&g_cnt[(C_HA + 2 * mt + kh) * 32], ep * 4); fence_async(); }
          if (s2 == S2A) { poll_ge(&g_cnt[(C_HB + 2 * mt + kh) * 32], ep * 4); fence_async(); }
          bulk_g2s(sb + s * SLOT2, hsrc + s2 * 4096, 8192, BAR(B_FULL2 + s));
          if (s2 == 7) {
            mbar_wait(BAR(B_FREEA + 9), 0);
            mbar_expect_tx(BAR(B_RES), 20480);
            tma2d(sb + SM_RES, &tmRes, 64 * mt, 160 * n4 + 80 * kh, BAR(B_RES));
            tma2d(sb + SM_RES + 10240, &tmRes, 1024 + 64 * mt, 160 * n4 + 80 * kh, BAR(B_RES));
            asm volatile("mbarrier.arrive.release.cluster.shared::cluster.b64 _, [%0];" ::"r"(mapa(BAR(B_XRDY), kh ^ 1)) : "memory");
          }
        }
      }
    } else {
      float s1[8], s2[8];
#pragma unroll
      for (int i = 0; i < 8; i++) { s1[i] = 0.f; s2[i] = 0.f; }
      const int rr = lane & 7, chunk = 2 * (jj & 3) + ((lane >> 3) & 1);
      const uint32_t a = sb + SM_A + (jj >> 2) * 8192 + ((lane >> 4) * 8 + rr) * 128 + ((chunk ^ rr) << 4);
#pragma unroll 1
      for (int k = 0; k < 40; k++) {
        if ((k & 3) == 0) mbar_wait(BAR(B_FULLA + (k >> 2)), 0);
        uint4 v = lds128(a + (k >> 2) * 16384 + (k & 3) * 2048);
        float e;
        e = bf_lo(v.x); s1[0] += e; s2[0] = fmaf(e, e, s2[0]); e = bf_hi(v.x); s1[1] += e; s2[1] = fmaf(e, e, s2[1]);
        e = bf_lo(v.y); s1[2] += e; s2[2] = fmaf(e, e, s2[2]); e = bf_hi(v.y); s1[3] += e; s2[3] = fmaf(e, e, s2[3]);
        e = bf_lo(v.z); s1[4] += e; s2[4] = fmaf(e, e, s2[4]); e = bf_hi(v.z); s1[5] += e; s2[5] = fmaf(e, e, s2[5]);
        e = bf_lo(v.w); s1[6] += e; s2[6] = fmaf(e, e, s2[6]); e = bf_hi(v.w); s1[7] += e; s2[7] = fmaf(e, e, s2[7]);
      }
#pragma unroll
      for (int i = 0; i < 8; i++) {
        s1[i] += __shfl_xor_sync(0xffffffffu, s1[i], 1); s2[i] += __shfl_xor_sync(0xffffffffu, s2[i], 1);
        s1[i] += __shfl_xor_sync(0xffffffffu, s1[i], 2); s2[i] += __shfl_xor_sync(0xffffffffu, s2[i], 2);
        s1[i] += __shfl_xor_sync(0xffffffffu, s1[i], 4); s2[i] += __shfl_xor_sync(0xffffffffu, s2[i], 4);
        s1[i] += __shfl_xor_sync(0xffffffffu, s1[i], 16); s2[i] += __shfl_xor_sync(0xffffffffu, s2[i], 16);
      }
      float a1 = s1[0], a2 = s2[0];
#pragma unroll
      for (int i = 1; i < 8; i++) { if (rr == i) { a1 = s1[i]; a2 = s2[i]; } }
      if (lane < 16) {
        float mean = a1 * (1.0f / DM);
        float var = fmaxf(a2 * (1.0f / DM) - mean * mean, 0.f);
        float r = rsqrtf(var + 1e-5f);
        g_st2[mt * 128 + 16 * jj + lane] = make_float2(r, -mean * r);
      }
      __syncwarp();
      if (lane == 0) red_release(&g_cnt[(C_ST + mt) * 32], 1);
    }
  }
}

typedef CUresult (*EncFn)(CUtensorMap*, CUtensorMapDataType, cuuint32_t, void*, const cuuint64_t*, const cuuint64_t*,
                          const cuuint32_t*, const cuuint32_t*, CUtensorMapInterleave, CUtensorMapSwizzle,
                          CUtensorMapL2promotion, CUtensorMapFloatOOBfill);

}

extern "C" void kernel_launch(void* const* d_in, const int* in_sizes, int n_in, void* d_out, int out_size) {
  (void)in_sizes; (void)n_in; (void)out_size;
  static EncFn enc = nullptr;
  static void* x1p = nullptr;
  if (!enc) {
    void* fn = nullptr; cudaDriverEntryPointQueryResult qr;
    cudaGetDriverEntryPoint("cuTensorMapEncodeTiled", &fn, cudaEnableDefault, &qr);
    enc = (EncFn)fn;
    cudaGetSymbolAddress(&x1p, g_x1T);
    cudaFuncSetAttribute(fused_kernel, cudaFuncAttributeMaxDynamicSharedMemorySize, SMEM_BYTES);
  }
  Params P;
  P.x = (const __nv_bfloat16*)d_in[0]; P.logA = (const __nv_bfloat16*)d_in[1]; P.Aim = (const __nv_bfloat16*)d_in[2];
  P.Cre = (const __nv_bfloat16*)d_in[3]; P.Cim = (const __nv_bfloat16*)d_in[4]; P.logdt = (const __nv_bfloat16*)d_in[5];
  P.Dskip = (const __nv_bfloat16*)d_in[6]; P.wg = (const __nv_bfloat16*)d_in[8]; P.wu = (const __nv_bfloat16*)d_in[9];
  P.wd = (const __nv_bfloat16*)d_in[10]; P.cvec = (const __nv_bfloat16*)d_in[11]; P.wmod = (const __nv_bfloat16*)d_in[12];
  P.out = (__nv_bfloat16*)d_out;
  CUtensorMap tmX1, tmRes, tmWd;
  {
    cuuint64_t dims[2] = {LSEQ, DM}; cuuint64_t str[1] = {LSEQ * 2}; cuuint32_t es[2] = {1, 1};
    cuuint32_t box[2] = {64, 64};
    enc(&tmX1, CU_TENSOR_MAP_DATA_TYPE_BFLOAT16, 2, x1p, dims, str, box, es, CU_TENSOR_MAP_INTERLEAVE_NONE,
        CU_TENSOR_MAP_SWIZZLE_128B, CU_TENSOR_MAP_L2_PROMOTION_NONE, CU_TENSOR_MAP_FLOAT_OOB_FILL_NONE);
    cuuint32_t box2[2] = {64, 80};
    enc(&tmRes, CU_TENSOR_MAP_DATA_TYPE_BFLOAT16, 2, x1p, dims, str, box2, es, CU_TENSOR_MAP_INTERLEAVE_NONE,
        CU_TENSOR_MAP_SWIZZLE_128B, CU_TENSOR_MAP_L2_PROMOTION_NONE, CU_TENSOR_MAP_FLOAT_OOB_FILL_NONE);
  }
  {
    cuuint64_t dims[3] = {32, DF, 20}; cuuint64_t str[2] = {DM * 2, 64}; cuuint32_t es[3] = {1, 1, 1};
    cuuint32_t box[3] = {32, 32, 5};
    enc(&tmWd, CU_TENSOR_MAP_DATA_TYPE_BFLOAT16, 3, (void*)P.wd, dims, str, box, es, CU_TENSOR_MAP_INTERLEAVE_NONE,
        CU_TENSOR_MAP_SWIZZLE_64B, CU_TENSOR_MAP_L2_PROMOTION_NONE, CU_TENSOR_MAP_FLOAT_OOB_FILL_NONE);
  }
  fused_kernel<<<NCTA, NTHR, SMEM_BYTES, cudaStreamPerThread>>>(P, tmX1, tmRes, tmWd);
}
```

```cpp
#include <cuda_runtime.h>
#include <cuda.h>
#include <cuda_bf16.h>
#include <cuda_fp16.h>
#include <stdint.h>
#include <string.h>

namespace {

constexpr int LSEQ = 2048, DM = 640, DF = 1728;
constexpr int NCTA = 128, NTHR = 384;
constexpr int FA = 120, FB = 96;
constexpr int NA = 2 * FA, NB = 2 * FB;
constexpr int TA_ = FA / 8, TB_ = FB / 8;
constexpr int BLOB_A = (DM + 16) * NA * 2, BLOB_B = (DM + 16) * NB * 2;
constexpr int TA1 = 8, TA2 = TA_ - TA1, TB1 = 4;
static_assert(TB_ == 12, "three pass-B segments of 4 tiles");
constexpr int BS2 = 32 * NB * 2;
#define KPRE 4
constexpr int S2A = 4 * FA / 32, S2B = 4 * FB / 32, S2 = S2A + S2B;

constexpr int G_XT = 0;
constexpr int G_VT = G_XT + DM * LSEQ * 2;
constexpr int G_X1T = G_VT + DM * LSEQ * 2;
constexpr int G_WP = G_X1T + DM * LSEQ * 2;
constexpr int G_WD = G_WP + 8 * (BLOB_A + BLOB_B);
constexpr int G_H = G_WD + DM * DF * 2;
constexpr int G_MOD = G_H + LSEQ * DF * 2;
constexpr int G_ST2 = G_MOD + 8192;
constexpr int G_CNT = G_ST2 + LSEQ * 8;
constexpr int G_END = G_CNT + 128 * 128;
__device__ __align__(1024) unsigned char g_buf[G_END];
#define STAMP(i)
#define STAMP1(i)
#define CSTAMP(i)
#define MARK(i)
constexpr int C_BAR1 = 0, C_MOD2 = 1, C_XF = 2, C_BAR2 = 3, C_WD = 4, C_MT = 32  , C_H = 0  ;

constexpr int SM_A = 0;
constexpr int SM_B = 163840;
constexpr int BST = 32 * NA * 2;
constexpr int SM_MISC = SM_B + 4 * BST;
constexpr int SLOT2 = 18432;
constexpr int SM_RES = 147456;
constexpr int SM_XR = SM_RES + 20480;
constexpr int SM_XS = 5 * SLOT2;
constexpr int SM_AX = SM_MISC;
constexpr int SM_BARS = SM_AX + 4096;
constexpr int SM_ST2 = SM_BARS + 688;
constexpr int SM_C0 = SM_ST2 + 512;
constexpr int SM_GB = SM_C0 + 128;
constexpr int SM_RED = SM_GB + 160;
constexpr int SM_LN2 = SM_AX + 512;
constexpr int SMEM_BYTES = SM_RED + 1024 + 320;
static_assert(SMEM_BYTES <= 232448, "smem");
constexpr int SM_X = 0, SM_V = 20480;
constexpr int SM_SC = 40960;
constexpr int SM_SB = SM_SC + 1280;
constexpr int SM_LN = SM_SB + 2560;
constexpr int SM_CB = SM_LN + 2048;
constexpr int HPL = 136 * 16;
constexpr int O_PT = 2 * HPL, O_KH = O_PT + 608 * 4, O_W = O_KH + 1312, WBS = 4640;
constexpr int U35 = 1600, U79 = 1088, O_U3 = O_W, O_U7 = O_W + 4 * U35, CBS = O_U7 + 4 * U79;
static_assert(CBS >= 16384 && O_W + 2 * WBS <= CBS && O_W + 4 * WBS <= 32768, "block");
static_assert(SM_CB + 4 * CBS + 32768 <= SM_B, "front smem");
constexpr int SM_WS = SM_B;
constexpr int SM_WM = SM_B + 40960;

enum { B_WS = 0, B_DATA = 1, B_SB = 2, B_STATS = 3, B_GB = 4, B_RES = 5, B_XRDY = 6, B_XFULL = 7, B_GO = 8, B_WM = 9, B_X = 10,
       B_XL = 85, B_ST = 11, B_STG = 12, B_SEG = 11  , B_FULLA = 16, B_FULL = 26  , B_N1 = 43, B_EMPTY = 43  , B_FREEA = 60, B_N2 = 70,
       B_H = 70  , B_DONE = 84, B_NUM = 85   };
constexpr int EMP = 8 * (B_EMPTY - B_FULL);

__device__ __forceinline__ uint32_t smem_u32(const void* p) { return (uint32_t)__cvta_generic_to_shared(p); }
__device__ __forceinline__ void mbar_init(uint32_t bar, int cnt) { asm volatile("mbarrier.init.shared::cta.b64 [%0], %1;" ::"r"(bar), "r"(cnt)); }
__device__ __forceinline__ void mbar_arrive(uint32_t bar) { asm volatile("mbarrier.arrive.shared::cta.b64 _, [%0];" ::"r"(bar) : "memory"); }
__device__ __forceinline__ void mbar_arrive_if(uint32_t bar, bool p) {
  asm volatile("{\n.reg .pred p;\nsetp.ne.u32 p, %1, 0;\n@p mbarrier.arrive.shared::cta.b64 _, [%0];\n}" ::"r"(bar), "r"((uint32_t)p) : "memory");
}
__device__ __forceinline__ void mbar_test(uint32_t bar, uint32_t parity) {
  asm volatile("mbarrier.test_wait.parity.shared::cta.b64 pnx, [%0], %1;" ::"r"(bar), "r"(parity) : "memory");
}
__device__ __forceinline__ void mbar_finish(uint32_t bar, uint32_t parity) {
  asm volatile("{\nLW:\n@!pnx mbarrier.try_wait.parity.shared::cta.b64 pnx, [%0], %1;\n@!pnx bra LW;\n}" ::"r"(bar), "r"(parity) : "memory");
}
__device__ __forceinline__ void mbar_expect_tx(uint32_t bar, uint32_t bytes) { asm volatile("mbarrier.arrive.expect_tx.shared::cta.b64 _, [%0], %1;" ::"r"(bar), "r"(bytes) : "memory"); }
__device__ __forceinline__ void mbar_wait_bounded(uint32_t bar, uint32_t parity) {
  asm volatile("{\n.reg .pred p;\n.reg .u32 c;\nmov.u32 c, 0;\nLW:\nmbarrier.try_wait.parity.acquire.cluster.shared::cta.b64 p, [%0], %1;\n@p bra LD;\nadd.u32 c, c, 1;\nsetp.lt.u32 p, c, 100000;\n@p bra LW;\ntrap;\nLD:\n}" ::"r"(bar), "r"(parity) : "memory");
}
__device__ __forceinline__ void mbar_wait(uint32_t bar, uint32_t parity) {
  asm volatile("{\n.reg .pred p;\nLW:\nmbarrier.try_wait.parity.shared::cta.b64 p, [%0], %1;\n@!p bra LW;\n}" ::"r"(bar), "r"(parity) : "memory");
}
__device__ __forceinline__ uint32_t mapa(uint32_t a, uint32_t cta) { uint32_t r; asm volatile("mapa.shared::cluster.u32 %0, %1, %2;" : "=r"(r) : "r"(a), "r"(cta)); return r; }
__device__ __forceinline__ void bulk_g2s(uint32_t dst, const void* src, uint32_t bytes, uint32_t bar) {
  asm volatile("cp.async.bulk.shared::cluster.global.mbarrier::complete_tx::bytes [%0], [%1], %2, [%3];" ::"r"(dst), "l"(src), "r"(bytes), "r"(bar) : "memory");
}
__device__ __forceinline__ void bulk_s2g(void* dst, uint32_t src, uint32_t bytes) {
  asm volatile("cp.async.bulk.global.shared::cta.bulk_group [%0], [%1], %2;" ::"l"(dst), "r"(src), "r"(bytes) : "memory");
}
__device__ __forceinline__ void tma2d(uint32_t dst, const CUtensorMap* tm, int c0, int c1, uint32_t bar) {
  asm volatile("cp.async.bulk.tensor.2d.shared::cluster.global.mbarrier::complete_tx::bytes [%0], [%1, {%3, %4}], [%2];" ::"r"(dst), "l"(tm), "r"(bar), "r"(c0), "r"(c1) : "memory");
}
__device__ __forceinline__ void tma3d(uint32_t dst, const CUtensorMap* tm, int c0, int c1, int c2, uint32_t bar) {
  asm volatile("cp.async.bulk.tensor.3d.shared::cluster.global.mbarrier::complete_tx::bytes [%0], [%1, {%3, %4, %5}], [%2];" ::"r"(dst), "l"(tm), "r"(bar), "r"(c0), "r"(c1), "r"(c2) : "memory");
}
__device__ __forceinline__ void tma3d_mc(uint32_t dst, const CUtensorMap* tm, int c0, int c1, int c2, uint32_t bar) {
  asm volatile("cp.async.bulk.tensor.3d.shared::cluster.global.mbarrier::complete_tx::bytes.multicast::cluster [%0], [%1, {%3, %4, %5}], [%2], %6;"
               ::"r"(dst), "l"(tm), "r"(bar), "r"(c0), "r"(c1), "r"(c2), "h"((unsigned short)3) : "memory");
}
__device__ __forceinline__ bool elect_one() {
  uint32_t p; asm volatile("{\n.reg .pred P;\nelect.sync _|P, 0xffffffff;\nselp.u32 %0, 1, 0, P;\n}" : "=r"(p)); return p;
}
__device__ __forceinline__ void tma2d_store(const CUtensorMap* tm, int c0, int c1, uint32_t src) {
  asm volatile("cp.async.bulk.tensor.2d.global.shared::cta.bulk_group [%0, {%2, %3}], [%1];" ::"l"(tm), "r"(src), "r"(c0), "r"(c1) : "memory");
}
__device__ __forceinline__ void bulk_commit() { asm volatile("cp.async.bulk.commit_group;" ::: "memory"); }
__device__ __forceinline__ void bulk_wait0() { asm volatile("cp.async.bulk.wait_group 0;" ::: "memory"); }
__device__ __forceinline__ void fence_async() { asm volatile("fence.proxy.async.global;" ::: "memory"); }
__device__ __forceinline__ void fence_async_smem() { asm volatile("fence.proxy.async.shared::cta;" ::: "memory"); }
__device__ __forceinline__ void nbar(int id, int n) { asm volatile("bar.sync %0, %1;" ::"r"(id), "r"(n) : "memory"); }
__device__ __forceinline__ unsigned* cnt(int i) { return (unsigned*)(g_buf + G_CNT) + i; }
__device__ __forceinline__ void red_release(int i) { asm volatile("red.release.gpu.global.add.u32 [%0], 1;" ::"l"(cnt(i)) : "memory"); }
__device__ __forceinline__ void red_relaxed(int i) { asm volatile("fence.proxy.async.global;\nred.relaxed.gpu.global.add.u32 [%0], 1;" ::"l"(cnt(i)) : "memory"); }
__device__ __forceinline__ void poll_ge(int i, unsigned target) {
  asm volatile("{\n.reg .pred p;\n.reg .u32 c, v;\nmov.u32 c, 0;\nLP:\nld.relaxed.gpu.global.u32 v, [%0];\nsub.u32 v, v, %1;\nsetp.ge.s32 p, v, 0;\n"
               "@p bra LD;\nadd.u32 c, c, 1;\nsetp.lt.u32 p, c, 2000000;\n@p bra LP;\ntrap;\nLD:\nfence.acquire.gpu;\nfence.proxy.async.global;\n}"
               ::"l"(cnt(i)), "r"(target) : "memory");
  __syncwarp();
}
__device__ __forceinline__ float ldg_mod(int i) {
  unsigned short v; asm volatile("ld.relaxed.gpu.global.u16 %0, [%1];" : "=h"(v) : "l"(g_buf + G_MOD + 2 * i) : "memory");
  return __uint_as_float((uint32_t)v << 16);
}
__device__ __forceinline__ void wg_fence() { asm volatile("wgmma.fence.sync.aligned;" ::: "memory"); }
__device__ __forceinline__ void wg_commit() { asm volatile("wgmma.commit_group.sync.aligned;" ::: "memory"); }
template <int N> __device__ __forceinline__ void wg_wait() { asm volatile("wgmma.wait_group.sync.aligned %0;" ::"n"(N) : "memory"); }
__device__ __forceinline__ uint64_t mkdesc(uint32_t addr, uint32_t lbo, uint32_t sbo, int swz) {
  return (uint64_t)((addr & 0x3FFFF) >> 4) | ((uint64_t)(lbo >> 4) << 16) | ((uint64_t)(sbo >> 4) << 32) | ((uint64_t)swz << 62);
}
__device__ __forceinline__ void ldsm4(uint32_t a, uint32_t& r0, uint32_t& r1, uint32_t& r2, uint32_t& r3) {
  asm volatile("ldmatrix.sync.aligned.m8n8.x4.shared.b16 {%0,%1,%2,%3}, [%4];" : "=r"(r0), "=r"(r1), "=r"(r2), "=r"(r3) : "r"(a) : "memory");
}
__device__ __forceinline__ void ldsm4t(uint32_t a, uint32_t& r0, uint32_t& r1, uint32_t& r2, uint32_t& r3) {
  asm volatile("ldmatrix.sync.aligned.m8n8.x4.trans.shared.b16 {%0,%1,%2,%3}, [%4];" : "=r"(r0), "=r"(r1), "=r"(r2), "=r"(r3) : "r"(a) : "memory");
}
__device__ __forceinline__ void stsm4t(uint32_t a, uint32_t r0, uint32_t r1, uint32_t r2, uint32_t r3) {
  asm volatile("stmatrix.sync.aligned.m8n8.x4.trans.shared.b16 [%0], {%1,%2,%3,%4};" ::"r"(a), "r"(r0), "r"(r1), "r"(r2), "r"(r3) : "memory");
}
__device__ __forceinline__ void stsm4(uint32_t a, uint32_t r0, uint32_t r1, uint32_t r2, uint32_t r3) {
  asm volatile("stmatrix.sync.aligned.m8n8.x4.shared.b16 [%0], {%1,%2,%3,%4};" ::"r"(a), "r"(r0), "r"(r1), "r"(r2), "r"(r3) : "memory");
}
__device__ __forceinline__ void mma_f16(float (&d)[4], uint32_t a0, uint32_t a1, uint32_t a2, uint32_t a3, uint32_t b0, uint32_t b1) {
  asm("mma.sync.aligned.m16n8k16.row.col.f32.f16.f16.f32 {%0,%1,%2,%3},{%4,%5,%6,%7},{%8,%9},{%0,%1,%2,%3};"
               : "+f"(d[0]), "+f"(d[1]), "+f"(d[2]), "+f"(d[3]) : "r"(a0), "r"(a1), "r"(a2), "r"(a3), "r"(b0), "r"(b1));
}
__device__ __forceinline__ void mma_bf16(float (&d)[4], uint32_t a0, uint32_t a1, uint32_t a2, uint32_t a3, uint32_t b0, uint32_t b1) {
  asm("mma.sync.aligned.m16n8k16.row.col.f32.bf16.bf16.f32 {%0,%1,%2,%3},{%4,%5,%6,%7},{%8,%9},{%0,%1,%2,%3};"
               : "+f"(d[0]), "+f"(d[1]), "+f"(d[2]), "+f"(d[3]) : "r"(a0), "r"(a1), "r"(a2), "r"(a3), "r"(b0), "r"(b1));
}
__device__ __forceinline__ uint32_t lds16(uint32_t a) { unsigned short v; asm volatile("ld.shared.u16 %0, [%1];" : "=h"(v) : "r"(a) : "memory"); return v; }
__device__ __forceinline__ float ldsbf(uint32_t a) { return __uint_as_float(lds16(a) << 16); }
__device__ __forceinline__ uint32_t lds32(uint32_t a) { uint32_t v; asm volatile("ld.shared.u32 %0, [%1];" : "=r"(v) : "r"(a) : "memory"); return v; }
__device__ __forceinline__ float ldsf(uint32_t a) { float v; asm volatile("ld.shared.f32 %0, [%1];" : "=f"(v) : "r"(a) : "memory"); return v; }
__device__ __forceinline__ float2 lds64f(uint32_t a) { float2 v; asm volatile("ld.shared.v2.f32 {%0,%1}, [%2];" : "=f"(v.x), "=f"(v.y) : "r"(a) : "memory"); return v; }
__device__ __forceinline__ float4 lds128f(uint32_t a) { float4 v; asm volatile("ld.shared.v4.f32 {%0,%1,%2,%3}, [%4];" : "=f"(v.x), "=f"(v.y), "=f"(v.z), "=f"(v.w) : "r"(a) : "memory"); return v; }
__device__ __forceinline__ uint4 lds128(uint32_t a) { uint4 v; asm volatile("ld.shared.v4.u32 {%0,%1,%2,%3}, [%4];" : "=r"(v.x), "=r"(v.y), "=r"(v.z), "=r"(v.w) : "r"(a) : "memory"); return v; }
__device__ __forceinline__ void sts16(uint32_t a, uint32_t v) { asm volatile("st.shared.u16 [%0], %1;" ::"r"(a), "h"((unsigned short)v) : "memory"); }
__device__ __forceinline__ void sts32(uint32_t a, uint32_t v) { asm volatile("st.shared.u32 [%0], %1;" ::"r"(a), "r"(v) : "memory"); }
__device__ __forceinline__ void stsf(uint32_t a, float v) { asm volatile("st.shared.f32 [%0], %1;" ::"r"(a), "f"(v) : "memory"); }
__device__ __forceinline__ void sts64f(uint32_t a, float x, float y) { asm volatile("st.shared.v2.f32 [%0], {%1,%2};" ::"r"(a), "f"(x), "f"(y) : "memory"); }
__device__ __forceinline__ void sts128f(uint32_t a, float x, float y, float z, float w) { asm volatile("st.shared.v4.f32 [%0], {%1,%2,%3,%4};" ::"r"(a), "f"(x), "f"(y), "f"(z), "f"(w) : "memory"); }
__device__ __forceinline__ void sts128(uint32_t a, uint4 v) { asm volatile("st.shared.v4.u32 [%0], {%1,%2,%3,%4};" ::"r"(a), "r"(v.x), "r"(v.y), "r"(v.z), "r"(v.w) : "memory"); }
__device__ __forceinline__ uint32_t pack_h2(float lo, float hi) { uint32_t r; asm("cvt.rn.f16x2.f32 %0, %1, %2;" : "=r"(r) : "f"(hi), "f"(lo)); return r; }
__device__ __forceinline__ uint32_t pack_bf2(float lo, float hi) { uint32_t r; asm("cvt.rn.bf16x2.f32 %0, %1, %2;" : "=r"(r) : "f"(hi), "f"(lo)); return r; }
__device__ __forceinline__ float bf_lo(uint32_t v) { return __uint_as_float(v << 16); }
__device__ __forceinline__ float bf_hi(uint32_t v) { return __uint_as_float(v & 0xffff0000u); }
__device__ __forceinline__ float bf16r(float x) { return bf_lo(pack_bf2(x, 0.f)); }
__device__ __forceinline__ float bfld(const __nv_bfloat16* p) { return __uint_as_float((uint32_t)__ldg((const unsigned short*)p) << 16); }
__device__ __forceinline__ float ex2f(float x) { float r; asm("ex2.approx.ftz.f32 %0, %1;" : "=f"(r) : "f"(x)); return r; }
__device__ __forceinline__ float rcpf(float x) { float r; asm("rcp.approx.ftz.f32 %0, %1;" : "=f"(r) : "f"(x)); return r; }
__device__ __forceinline__ float rsqf(float x) { float r; asm("rsqrt.approx.ftz.f32 %0, %1;" : "=f"(r) : "f"(x)); return r; }
__device__ __forceinline__ float tanhf_(float x) { float r; asm("tanh.approx.f32 %0, %1;" : "=f"(r) : "f"(x)); return r; }
__device__ __forceinline__ uint32_t hmul2_bf(uint32_t a, uint32_t b) { uint32_t r; asm("mul.rn.bf16x2 %0, %1, %2;" : "=r"(r) : "r"(a), "r"(b)); return r; }
__device__ __forceinline__ uint32_t hfma2_h(uint32_t a, uint32_t b, uint32_t c) { uint32_t r; asm("fma.rn.f16x2 %0, %1, %2, %3;" : "=r"(r) : "r"(a), "r"(b), "r"(c)); return r; }
__device__ __forceinline__ uint32_t hadd2_h(uint32_t a, uint32_t b) { uint32_t r; asm("add.rn.f16x2 %0, %1, %2;" : "=r"(r) : "r"(a), "r"(b)); return r; }
__device__ __forceinline__ uint32_t movm(uint32_t a) { uint32_t r; asm volatile("movmatrix.sync.aligned.m8n8.trans.b16 %0, %1;" : "=r"(r) : "r"(a)); return r; }
__device__ __forceinline__ uint2 lds64(uint32_t a) { uint2 v; asm volatile("ld.shared.v2.u32 {%0,%1}, [%2];" : "=r"(v.x), "=r"(v.y) : "r"(a) : "memory"); return v; }
__device__ __forceinline__ void cpasync16(uint32_t dst, const void* src) { asm volatile("cp.async.cg.shared.global [%0], [%1], 16;" ::"r"(dst), "l"(src) : "memory"); }
constexpr float LOG2E = 1.4426950408889634f, TWO_PI = 6.283185307179586f;
struct cf { float r, i; };
__device__ __forceinline__ cf cmul(cf a, cf b) { cf o; o.r = fmaf(a.r, b.r, -(a.i * b.i)); o.i = fmaf(a.r, b.i, a.i * b.r); return o; }
__device__ __forceinline__ cf cmulc(cf a, cf b) { cf o; o.r = fmaf(a.r, b.r, a.i * b.i); o.i = fmaf(a.i, b.r, -(a.r * b.i)); return o; }
__device__ __forceinline__ cf csq(cf a) { cf o; o.r = fmaf(a.r, a.r, -(a.i * a.i)); o.i = (a.r + a.r) * a.i; return o; }

template<int N> struct WG;
template<int TA, int TB> __device__ __forceinline__ void wgmma_ss_240(float (&d)[120], uint64_t da, uint64_t db, int sd) {
  asm volatile("{\n.reg .pred p;\nsetp.ne.b32 p, %122, 0;\n"
  "wgmma.mma_async.sync.aligned.m64n240k16.f32.bf16.bf16 {%0, %1, %2, %3, %4, %5, %6, %7, %8, %9, %10, %11, %12, %13, %14, %15, %16, %17, %18, %19, %20, %21, %22, %23, %24, %25, %26, %27, %28, %29, %30, %31, %32, %33, %34, %35, %36, %37, %38, %39, %40, %41, %42, %43, %44, %45, %46, %47, %48, %49, %50, %51, %52, %53, %54, %55, %56, %57, %58, %59, %60, %61, %62, %63, %64, %65, %66, %67, %68, %69, %70, %71, %72, %73, %74, %75, %76, %77, %78, %79, %80, %81, %82, %83, %84, %85, %86, %87, %88, %89, %90, %91, %92, %93, %94, %95, %96, %97, %98, %99, %100, %101, %102, %103, %104, %105, %106, %107, %108, %109, %110, %111, %112, %113, %114, %115, %116, %117, %118, %119}, %120, %121, p, 1, 1, %123, %124;\n}\n"
  : "+f"(d[0]), "+f"(d[1]), "+f"(d[2]), "+f"(d[3]), "+f"(d[4]), "+f"(d[5]), "+f"(d[6]), "+f"(d[7]), "+f"(d[8]), "+f"(d[9]), "+f"(d[10]), "+f"(d[11]), "+f"(d[12]), "+f"(d[13]), "+f"(d[14]), "+f"(d[15]), "+f"(d[16]), "+f"(d[17]), "+f"(d[18]), "+f"(d[19]), "+f"(d[20]), "+f"(d[21]), "+f"(d[22]), "+f"(d[23]), "+f"(d[24]), "+f"(d[25]), "+f"(d[26]), "+f"(d[27]), "+f"(d[28]), "+f"(d[29]), "+f"(d[30]), "+f"(d[31]), "+f"(d[32]), "+f"(d[33]), "+f"(d[34]), "+f"(d[35]), "+f"(d[36]), "+f"(d[37]), "+f"(d[38]), "+f"(d[39]), "+f"(d[40]), "+f"(d[41]), "+f"(d[42]), "+f"(d[43]), "+f"(d[44]), "+f"(d[45]), "+f"(d[46]), "+f"(d[47]), "+f"(d[48]), "+f"(d[49]), "+f"(d[50]), "+f"(d[51]), "+f"(d[52]), "+f"(d[53]), "+f"(d[54]), "+f"(d[55]), "+f"(d[56]), "+f"(d[57]), "+f"(d[58]), "+f"(d[59]), "+f"(d[60]), "+f"(d[61]), "+f"(d[62]), "+f"(d[63]), "+f"(d[64]), "+f"(d[65]), "+f"(d[66]), "+f"(d[67]), "+f"(d[68]), "+f"(d[69]), "+f"(d[70]), "+f"(d[71]), "+f"(d[72]), "+f"(d[73]), "+f"(d[74]), "+f"(d[75]), "+f"(d[76]), "+f"(d[77]), "+f"(d[78]), "+f"(d[79]), "+f"(d[80]), "+f"(d[81]), "+f"(d[82]), "+f"(d[83]), "+f"(d[84]), "+f"(d[85]), "+f"(d[86]), "+f"(d[87]), "+f"(d[88]), "+f"(d[89]), "+f"(d[90]), "+f"(d[91]), "+f"(d[92]), "+f"(d[93]), "+f"(d[94]), "+f"(d[95]), "+f"(d[96]), "+f"(d[97]), "+f"(d[98]), "+f"(d[99]), "+f"(d[100]), "+f"(d[101]), "+f"(d[102]), "+f"(d[103]), "+f"(d[104]), "+f"(d[105]), "+f"(d[106]), "+f"(d[107]), "+f"(d[108]), "+f"(d[109]), "+f"(d[110]), "+f"(d[111]), "+f"(d[112]), "+f"(d[113]), "+f"(d[114]), "+f"(d[115]), "+f"(d[116]), "+f"(d[117]), "+f"(d[118]), "+f"(d[119])
  : "l"(da), "l"(db), "r"(sd), "n"(TA), "n"(TB));
}
template<> struct WG<240> { template<int TA,int TB> static __device__ __forceinline__ void ss(float (&d)[120], uint64_t da, uint64_t db, int sd) { wgmma_ss_240<TA,TB>(d,da,db,sd); } };
template<int TA, int TB> __device__ __forceinline__ void wgmma_ss_192(float (&d)[96], uint64_t da, uint64_t db, int sd) {
  asm volatile("{\n.reg .pred p;\nsetp.ne.b32 p, %98, 0;\n"
  "wgmma.mma_async.sync.aligned.m64n192k16.f32.bf16.bf16 {%0, %1, %2, %3, %4, %5, %6, %7, %8, %9, %10, %11, %12, %13, %14, %15, %16, %17, %18, %19, %20, %21, %22, %23, %24, %25, %26, %27, %28, %29, %30, %31, %32, %33, %34, %35, %36, %37, %38, %39, %40, %41, %42, %43, %44, %45, %46, %47, %48, %49, %50, %51, %52, %53, %54, %55, %56, %57, %58, %59, %60, %61, %62, %63, %64, %65, %66, %67, %68, %69, %70, %71, %72, %73, %74, %75, %76, %77, %78, %79, %80, %81, %82, %83, %84, %85, %86, %87, %88, %89, %90, %91, %92, %93, %94, %95}, %96, %97, p, 1, 1, %99, %100;\n}\n"
  : "+f"(d[0]), "+f"(d[1]), "+f"(d[2]), "+f"(d[3]), "+f"(d[4]), "+f"(d[5]), "+f"(d[6]), "+f"(d[7]), "+f"(d[8]), "+f"(d[9]), "+f"(d[10]), "+f"(d[11]), "+f"(d[12]), "+f"(d[13]), "+f"(d[14]), "+f"(d[15]), "+f"(d[16]), "+f"(d[17]), "+f"(d[18]), "+f"(d[19]), "+f"(d[20]), "+f"(d[21]), "+f"(d[22]), "+f"(d[23]), "+f"(d[24]), "+f"(d[25]), "+f"(d[26]), "+f"(d[27]), "+f"(d[28]), "+f"(d[29]), "+f"(d[30]), "+f"(d[31]), "+f"(d[32]), "+f"(d[33]), "+f"(d[34]), "+f"(d[35]), "+f"(d[36]), "+f"(d[37]), "+f"(d[38]), "+f"(d[39]), "+f"(d[40]), "+f"(d[41]), "+f"(d[42]), "+f"(d[43]), "+f"(d[44]), "+f"(d[45]), "+f"(d[46]), "+f"(d[47]), "+f"(d[48]), "+f"(d[49]), "+f"(d[50]), "+f"(d[51]), "+f"(d[52]), "+f"(d[53]), "+f"(d[54]), "+f"(d[55]), "+f"(d[56]), "+f"(d[57]), "+f"(d[58]), "+f"(d[59]), "+f"(d[60]), "+f"(d[61]), "+f"(d[62]), "+f"(d[63]), "+f"(d[64]), "+f"(d[65]), "+f"(d[66]), "+f"(d[67]), "+f"(d[68]), "+f"(d[69]), "+f"(d[70]), "+f"(d[71]), "+f"(d[72]), "+f"(d[73]), "+f"(d[74]), "+f"(d[75]), "+f"(d[76]), "+f"(d[77]), "+f"(d[78]), "+f"(d[79]), "+f"(d[80]), "+f"(d[81]), "+f"(d[82]), "+f"(d[83]), "+f"(d[84]), "+f"(d[85]), "+f"(d[86]), "+f"(d[87]), "+f"(d[88]), "+f"(d[89]), "+f"(d[90]), "+f"(d[91]), "+f"(d[92]), "+f"(d[93]), "+f"(d[94]), "+f"(d[95])
  : "l"(da), "l"(db), "r"(sd), "n"(TA), "n"(TB));
}
template<> struct WG<192> { template<int TA,int TB> static __device__ __forceinline__ void ss(float (&d)[96], uint64_t da, uint64_t db, int sd) { wgmma_ss_192<TA,TB>(d,da,db,sd); } };
template<int TA, int TB> __device__ __forceinline__ void wgmma_ss_160(float (&d)[80], uint64_t da, uint64_t db, int sd) {
  asm volatile("{\n.reg .pred p;\nsetp.ne.b32 p, %82, 0;\n"
  "wgmma.mma_async.sync.aligned.m64n160k16.f32.bf16.bf16 {%0, %1, %2, %3, %4, %5, %6, %7, %8, %9, %10, %11, %12, %13, %14, %15, %16, %17, %18, %19, %20, %21, %22, %23, %24, %25, %26, %27, %28, %29, %30, %31, %32, %33, %34, %35, %36, %37, %38, %39, %40, %41, %42, %43, %44, %45, %46, %47, %48, %49, %50, %51, %52, %53, %54, %55, %56, %57, %58, %59, %60, %61, %62, %63, %64, %65, %66, %67, %68, %69, %70, %71, %72, %73, %74, %75, %76, %77, %78, %79}, %80, %81, p, 1, 1, %83, %84;\n}\n"
  : "+f"(d[0]), "+f"(d[1]), "+f"(d[2]), "+f"(d[3]), "+f"(d[4]), "+f"(d[5]), "+f"(d[6]), "+f"(d[7]), "+f"(d[8]), "+f"(d[9]), "+f"(d[10]), "+f"(d[11]), "+f"(d[12]), "+f"(d[13]), "+f"(d[14]), "+f"(d[15]), "+f"(d[16]), "+f"(d[17]), "+f"(d[18]), "+f"(d[19]), "+f"(d[20]), "+f"(d[21]), "+f"(d[22]), "+f"(d[23]), "+f"(d[24]), "+f"(d[25]), "+f"(d[26]), "+f"(d[27]), "+f"(d[28]), "+f"(d[29]), "+f"(d[30]), "+f"(d[31]), "+f"(d[32]), "+f"(d[33]), "+f"(d[34]), "+f"(d[35]), "+f"(d[36]), "+f"(d[37]), "+f"(d[38]), "+f"(d[39]), "+f"(d[40]), "+f"(d[41]), "+f"(d[42]), "+f"(d[43]), "+f"(d[44]), "+f"(d[45]), "+f"(d[46]), "+f"(d[47]), "+f"(d[48]), "+f"(d[49]), "+f"(d[50]), "+f"(d[51]), "+f"(d[52]), "+f"(d[53]), "+f"(d[54]), "+f"(d[55]), "+f"(d[56]), "+f"(d[57]), "+f"(d[58]), "+f"(d[59]), "+f"(d[60]), "+f"(d[61]), "+f"(d[62]), "+f"(d[63]), "+f"(d[64]), "+f"(d[65]), "+f"(d[66]), "+f"(d[67]), "+f"(d[68]), "+f"(d[69]), "+f"(d[70]), "+f"(d[71]), "+f"(d[72]), "+f"(d[73]), "+f"(d[74]), "+f"(d[75]), "+f"(d[76]), "+f"(d[77]), "+f"(d[78]), "+f"(d[79])
  : "l"(da), "l"(db), "r"(sd), "n"(TA), "n"(TB));
}
template<> struct WG<160> { template<int TA,int TB> static __device__ __forceinline__ void ss(float (&d)[80], uint64_t da, uint64_t db, int sd) { wgmma_ss_160<TA,TB>(d,da,db,sd); } };

struct Params {
  const __nv_bfloat16 *x, *logA, *Aim, *Cre, *Cim, *logdt, *Dskip, *wd, *cvec, *wmod, *wg, *wu;
  __nv_bfloat16* out;
};

__device__ __noinline__ void gemv_wave(uint32_t sb, int wave) {
  const int ht = threadIdx.x - 256, lane = ht & 31, hw = ht >> 5;
  if (wave) mbar_wait(sb + SM_BARS + 8 * B_WM, 0);
  else { asm volatile("cp.async.wait_all;" ::: "memory"); nbar(7, 128); }
  float d0[4] = {0.f, 0.f, 0.f, 0.f}, d1[4] = {0.f, 0.f, 0.f, 0.f};
  uint32_t a = sb + SM_WM + (hw * 160 + (lane & 15)) * 32 + (lane >> 4) * 16;
  uint32_t s = sb + SM_SC + hw * 320 + (lane & 3) * 4;
#pragma unroll 1
  for (int k5 = 0; k5 < 2; k5++) {
    uint32_t b[5][4], av[5][2];
#pragma unroll
    for (int ks = 0; ks < 5; ks++) {
      ldsm4t(a + (k5 * 5 + ks) * 512, b[ks][0], b[ks][1], b[ks][2], b[ks][3]);
      av[ks][0] = lds32(s + (k5 * 5 + ks) * 32); av[ks][1] = lds32(s + (k5 * 5 + ks) * 32 + 16);
    }
#pragma unroll
    for (int ks = 0; ks < 5; ks++) {
      mma_bf16(d0, av[ks][0], 0u, av[ks][1], 0u, b[ks][0], b[ks][1]);
      mma_bf16(d1, av[ks][0], 0u, av[ks][1], 0u, b[ks][2], b[ks][3]);
    }
  }
  if (lane < 4) { sts64f(sb + SM_RED + hw * 64 + lane * 8, d0[0], d0[1]); sts64f(sb + SM_RED + hw * 64 + 32 + lane * 8, d1[0], d1[1]); }
  nbar(7, 128);
  if (ht < 16) {
    uint32_t r = sb + SM_RED + ht * 4;
    float v = bf16r((ldsf(r) + ldsf(r + 64)) + (ldsf(r + 128) + ldsf(r + 192)));
    const int cl = 16 * blockIdx.x + ht;
    if (cl >= DM && cl < 2 * DM) v += 1.0f;
    sts16(sb + SM_RED + 256 + ht * 2, pack_bf2(v, 0.f));
    fence_async_smem();
  }
  nbar(7, 128);
}

__global__ void __cluster_dims__(2, 1, 1) __launch_bounds__(NTHR, 1)
fused_kernel(const __grid_constant__ Params P, const __grid_constant__ CUtensorMap tmX1, const __grid_constant__ CUtensorMap tmRes,
             const __grid_constant__ CUtensorMap tmXV, const __grid_constant__ CUtensorMap tmX, const __grid_constant__ CUtensorMap tmWm,
             const __grid_constant__ CUtensorMap tmWg, const __grid_constant__ CUtensorMap tmWu) {
  extern __shared__ __align__(1024) unsigned char smem_raw[];
  asm volatile(".reg .pred pnx;");
  uint32_t sb = smem_u32(smem_raw);
  asm volatile("mov.u32 %0, %0;" : "+r"(sb));
  sb = __shfl_sync(0xffffffffu, sb, 0);
  const int tid = threadIdx.x, lane = tid & 31;
  const int warp = __shfl_sync(0xffffffffu, tid >> 5, 0);
  const int c = blockIdx.x;
  const int g = lane >> 2, q4 = lane & 3, ht = tid - 256;
  const uint32_t bars = sb + SM_BARS;
  auto BAR = [&](int i) { return bars + 8 * i; };
  if (warp == 0) STAMP(0);

  const int kh = c & 1, n4 = (c >> 1) & 3, mt = c >> 3, jj = 4 * kh + n4;
  if (warp == 11) {
    if (elect_one()) {
      mbar_init(BAR(B_XL), 1);
      fence_async_smem();
      mbar_expect_tx(BAR(B_XL), 40960);
      asm volatile("cp.async.bulk.tensor.5d.shared::cluster.global.mbarrier::complete_tx::bytes [%0], [%1, {%3, %3, %4, %3, %5}], [%2];"
                   ::"r"(sb + SM_WS), "l"(&tmX), "r"(BAR(B_XL)), "r"(0), "r"(4 * ((c >> 1) & 31)), "r"(c >> 6) : "memory");
    }
    __syncwarp();
  }
  const int ch = warp < 8 ? (warp & 3) : 4;
  const int part = warp < 8 ? (warp >> 2) : (warp & 3);
  const int lsp = warp < 8 ? 1 : 2;
  const int dch = 5 * c + ch;
  float pla[2], pai[2], pcr[2], pci[2];
#pragma unroll
  for (int i = 0; i < 2; i++) {
    const int n = dch * 128 + part * (128 >> lsp) + ((i * 32) & ((128 >> lsp) - 1)) + lane;
    pla[i] = bfld(P.logA + n); pai[i] = bfld(P.Aim + n); pcr[i] = bfld(P.Cre + n); pci[i] = bfld(P.Cim + n);
  }
  const uint4 call = __ldg((const uint4*)((lane < 16 ? P.Cre : P.Cim) + dch * 128) + (lane & 15));
  const float pdt = bfld(P.logdt + dch), pD = bfld(P.Dskip + dch);
  unsigned csnap;
  asm volatile("ld.relaxed.gpu.global.u32 %0, [%1];" : "=r"(csnap) : "l"(cnt(lane < 16 ? lane : C_MT + 32 * mt + lane - 16)) : "memory");
  const uint2 cva = __ldg((const uint2*)(P.cvec + 4 * (tid & 127))), cvb = __ldg((const uint2*)(P.cvec + 512 + 4 * lane));
  if (warp >= 8) {
    {
      const __nv_bfloat16* src = P.wmod + (ht >> 1) * 3840 + 16 * c + (ht & 1) * 8;
#pragma unroll
      for (int it = 0; it < 10; it++) cpasync16(sb + SM_WM + ht * 16 + it * 2048, src + it * 64 * 3840);
    }
    if (warp == 11 && elect_one()) {
#pragma unroll
      for (int i = 0; i < B_NUM; i++) mbar_init(BAR(i), i < B_N1 ? 1 : i < B_N2 ? 2 : 8);
      asm volatile("fence.mbarrier_init.release.cluster;" ::: "memory");
    }
    if (warp == 9 && elect_one()) {
      asm volatile("prefetch.tensormap [%0];" ::"l"(&tmXV) : "memory");
      asm volatile("prefetch.tensormap [%0];" ::"l"(&tmWm) : "memory");
      asm volatile("prefetch.tensormap [%0];" ::"l"(c >= 54 ? &tmWu : &tmWg) : "memory");
      asm volatile("prefetch.tensormap [%0];" ::"l"(&tmX1) : "memory");
      asm volatile("prefetch.tensormap [%0];" ::"l"(&tmRes) : "memory");
    }
  }
  if (sb & 1023u) __trap();
  asm volatile("barrier.cluster.arrive.relaxed.aligned;" ::: "memory");
  __syncthreads();
  MARK(1);
  {
    const int gsz = 32 << lsp, gtid = part * 32 + lane, barid = 1 + ch;
    const uint32_t cb = sb + SM_CB + ch * CBS;
    const uint32_t tab = cb + O_W + part * WBS;
    const float dt = bf16r(ex2f(pdt * LOG2E));
    float scC;
    {
      const uint32_t m = max(max(max(call.x & 0x7fffu, call.y & 0x7fffu), max(call.z & 0x7fffu, call.w & 0x7fffu)) << 16,
                             max(max(call.x & 0x7fff0000u, call.y & 0x7fff0000u), max(call.z & 0x7fff0000u, call.w & 0x7fff0000u)));
      scC = fmaxf(__uint_as_float(__reduce_max_sync(0xffffffffu, m)), 1e-30f);
    }
    if (warp == 0) STAMP(20);
    const float iscC = rcpf(scC);
    float k2048 = 0.f;
#pragma unroll 1
    for (int i = 0; i < (4 >> lsp); i++) {
      const float lr2 = -bf16r(ex2f(pla[0] * LOG2E)) * dt * LOG2E;
      float th = pai[0] * dt * 0.15915494309189535f; th -= rintf(th);
      const float cr = pcr[0] * iscC, ci = pci[0] * iscC;
      float zr[3], zi[3];
#pragma unroll
      for (int e = 0; e < 3; e++) {
        const float p = e == 0 ? 8.f : e == 1 ? 128.f : 2048.f;
        const float m = ex2f(lr2 * p); float an = th * p; an = (an - rintf(an)) * TWO_PI;
        zr[e] = m * __cosf(an); zi[e] = m * __sinf(an);
      }
      const uint32_t o = tab + (i * 32 + lane) * 32;
      sts128f(o, lr2, th * TWO_PI, cr, -ci);
      sts128f(o + 16, zr[0], zi[0], zr[1], zi[1]);
      k2048 += cr * zr[2] - ci * zi[2];
      pla[0] = pla[1]; pai[0] = pai[1]; pcr[0] = pcr[1]; pci[0] = pci[1];
    }
    __syncwarp();
    if (warp == 0) STAMP(25);
    MARK(2);
    float T[5][4];
#pragma unroll
    for (int s = 0; s < 5; s++) { T[s][0] = T[s][1] = T[s][2] = T[s][3] = 0.f; }
    const float gf = (float)g;
    int ks = 0;
#pragma unroll 1
    for (int ph = 0; ph < 2; ph++) {
      const int kend = ph ? (16 >> lsp) : (KPRE >> lsp);
#pragma unroll 1
      for (; ks < kend; ks++) {
        uint32_t A[4][4], B[5][2];
#pragma unroll
        for (int h = 0; h < 2; h++) {
          const uint32_t a = tab + (ks * 8 + q4 + 4 * h) * 32;
          const float4 s0 = lds128f(a), s1 = lds128f(a + 16);
          const float m = ex2f(s0.x * gf), an = s0.y * gf;
          cf u; u.r = m * __cosf(an); u.i = m * __sinf(an);
          cf z8; z8.r = s1.x; z8.i = s1.y; cf z128; z128.r = s1.z; z128.i = s1.w; cf b; b.r = s0.z; b.i = s0.w;
          cf u2 = cmul(u, z8);
          A[0][2 * h] = pack_h2(u.r, u.i); A[0][2 * h + 1] = pack_h2(u2.r, u2.i);
#pragma unroll
          for (int k = 1; k < 4; k++) { u = csq(u); u2 = csq(u2); A[k][2 * h] = pack_h2(u.r, u.i); A[k][2 * h + 1] = pack_h2(u2.r, u2.i); }
          cf w = csq(u);
          b = cmulc(b, w); B[0][h] = pack_h2(b.r, b.i);
          b = cmulc(b, z128); B[1][h] = pack_h2(b.r, b.i);
          w = cmul(w, z128);
          b = cmulc(b, w); B[2][h] = pack_h2(b.r, b.i);
          w = csq(w);
          b = cmulc(b, w); B[3][h] = pack_h2(b.r, b.i);
          w = csq(w);
          b = cmulc(b, w); B[4][h] = pack_h2(b.r, b.i);
        }
        mma_f16(T[0], A[0][0], A[0][1], A[0][2], A[0][3], B[0][0], B[0][1]);
        mma_f16(T[1], A[0][0], A[0][1], A[0][2], A[0][3], B[1][0], B[1][1]);
        mma_f16(T[2], A[1][0], A[1][1], A[1][2], A[1][3], B[2][0], B[2][1]);
        mma_f16(T[3], A[2][0], A[2][1], A[2][2], A[2][3], B[3][0], B[3][1]);
        mma_f16(T[4], A[3][0], A[3][1], A[3][2], A[3][3], B[4][0], B[4][1]);
      }
      if (ph) break;
      MARK(3);
      if (warp == 0) STAMP(21);
      if (warp < 8) {
        mbar_wait(BAR(B_XL), 0);
        if (warp == 0) STAMP(34);
        const uint32_t xl = sb + SM_WS + (lane & 15) * 128;
#pragma unroll
        for (int m2 = 0; m2 < 2; m2++) {
          float D0[4] = {0.f, 0.f, 0.f, 0.f}, D1[4] = {0.f, 0.f, 0.f, 0.f}, DS[4] = {0.f, 0.f, 0.f, 0.f};
          uint32_t a[5][4];
#pragma unroll
          for (int k = 0; k < 5; k++) {
            const int ks = 5 * warp + k;
            ldsm4(xl + (ks >> 2) * 4096 + m2 * 2048 + (((2 * (ks & 3) + (lane >> 4)) ^ (lane & 7)) << 4), a[k][0], a[k][1], a[k][2], a[k][3]);
          }
#pragma unroll
          for (int k = 0; k < 5; k++) {
            mma_bf16(D0, a[k][0], a[k][1], a[k][2], a[k][3], a[k][0], a[k][2]);
            mma_bf16(D1, a[k][0], a[k][1], a[k][2], a[k][3], a[k][1], a[k][3]);
            mma_bf16(DS, a[k][0], a[k][1], a[k][2], a[k][3], 0x3f803f80u, 0x3f803f80u);
          }
          if (q4 == (g >> 1)) sts128f(sb + SM_LN + m2 * 1024 + warp * 128 + g * 16, DS[0], (g & 1) ? D0[1] : D0[0], DS[2], (g & 1) ? D1[3] : D1[2]);
        }
        uint32_t xf[5][4];
        const uint32_t ta = sb + (80 * (warp >> 1) + 8 * (lane >> 4) + (lane & 7)) * 64 + (((2 * (warp & 1) + ((lane >> 3) & 1)) ^ ((lane >> 1) & 3)) << 4);
#pragma unroll
        for (int k = 0; k < 5; k++) {
          const int ks = 20 * kh + 5 * (warp >> 1) + k;
          ldsm4(xl + (ks >> 2) * 4096 + (warp & 1) * 2048 + (((2 * (ks & 3) + (lane >> 4)) ^ (lane & 7)) << 4), xf[k][0], xf[k][1], xf[k][2], xf[k][3]);
        }
#pragma unroll
        for (int k = 0; k < 5; k++) stsm4t(ta + SM_X + k * 1024, xf[k][0], xf[k][1], xf[k][2], xf[k][3]);
        nbar(8, 256);
        const uint32_t ln = sb + SM_LN + (warp & 1) * 1024 + g * 16;
        float4 s = lds128f(ln);
#pragma unroll
        for (int w = 1; w < 8; w++) { const float4 v = lds128f(ln + w * 128); s.x += v.x; s.y += v.y; s.z += v.z; s.w += v.w; }
        s.x *= (1.0f / DM); s.z *= (1.0f / DM);
        const float ra = rsqf(fmaxf(fmaf(s.y, 1.0f / DM, -s.x * s.x), 0.f) + 1e-5f), ma = -s.x * ra;
        const float rb = rsqf(fmaxf(fmaf(s.w, 1.0f / DM, -s.z * s.z), 0.f) + 1e-5f), mb = -s.z * rb;
        auto nrm = [](uint32_t w, float r, float m) { return pack_h2(fmaf(bf_lo(w), r, m), fmaf(bf_hi(w), r, m)); };
#pragma unroll
        for (int k = 0; k < 5; k++) stsm4t(ta + SM_V + k * 1024, nrm(xf[k][0], ra, ma), nrm(xf[k][1], rb, mb), nrm(xf[k][2], ra, ma), nrm(xf[k][3], rb, mb));
        fence_async_smem();
      } else {
        auto silu2 = [](uint32_t w) {
          const float a = bf_lo(w), b = bf_hi(w);
          return pack_bf2(a * rcpf(1.0f + ex2f(-LOG2E * a)), b * rcpf(1.0f + ex2f(-LOG2E * b)));
        };
        asm volatile("st.shared.v2.u32 [%0], {%1,%2};" ::"r"(sb + SM_SC + ht * 8), "r"(silu2(cva.x)), "r"(silu2(cva.y)) : "memory");
        asm volatile("st.shared.v2.u32 [%0], {%1,%2};" ::"r"(sb + SM_SC + 1024 + lane * 8), "r"(silu2(cvb.x)), "r"(silu2(cvb.y)) : "memory");
        if (warp == 8) sts32(sb + SM_C0 + lane * 4, csnap);
        if (warp == 8) STAMP(30);
        asm volatile("cp.async.wait_all;" ::: "memory");
        if (warp == 8) STAMP(31);
        gemv_wave(sb, 0);
        if (warp == 9 && elect_one()) {
#pragma unroll
          for (int i = 0; i < 5; i++)
            asm volatile("cp.async.bulk.prefetch.L2.global [%0], %1;" ::"l"(P.wmod + (5 * c + i) * 3840 + 1920), "r"(3840) : "memory");
          asm volatile("cp.async.bulk.prefetch.L2.global [%0], %1;" ::"l"((const char*)(c < 64 ? P.wg : P.wu) + (c & 63) * 34560), "r"(34560) : "memory");
        }
        if (warp == 8) STAMP(32);
      }
      MARK(4);
      if (warp == 0) STAMP(22);
      asm volatile("barrier.cluster.wait.aligned;" ::: "memory");
      __syncthreads();
      if (warp == 0) STAMP(33);
      if (warp == 8) {
        fence_async_smem();
        if (elect_one()) {
#pragma unroll
          for (int i = 0; i < 2; i++) tma2d_store(&tmXV, 32 * (c >> 1), DM + 320 * kh + i * 160, sb + SM_V + i * 10240);
          if (c < 120) bulk_s2g(g_buf + G_MOD + 32 * c, sb + SM_RED + 256, 32);
          bulk_commit();
        }
        __syncwarp();
        asm volatile("bar.arrive 9, 64;" ::: "memory");
      }
      if (warp == 9) {
        nbar(9, 64);
        if (elect_one()) {
          mbar_expect_tx(BAR(B_WM), 20480);
#pragma unroll
          for (int i = 0; i < 4; i++) tma2d(sb + SM_WM + i * 5120, &tmWm, 1920 + 16 * c, i * 160, BAR(B_WM));
          mbar_expect_tx(BAR(B_WS), 40960);
#pragma unroll
          for (int i = 0; i < 4; i++) tma2d(sb + SM_WS + i * 10240, c >= 54 ? &tmWu : &tmWg, 32 * (c >= 54 ? c - 54 : c), i * 160, BAR(B_WS));
        }
        __syncwarp();
      }
    }
    if (warp == 8) {
      __syncwarp();
      if (elect_one()) {
        STAMP1(29);
        bulk_wait0();
        STAMP1(26);
        red_relaxed(C_BAR1);
        STAMP1(1);
      }
      __syncwarp();
    }
    if (warp >= 8) {
      gemv_wave(sb, 1);
      if (warp == 8) {
        poll_ge(C_BAR1, (lds32(sb + SM_C0) & ~127u) + 128);
        STAMP(16);
        if (elect_one()) {
          mbar_expect_tx(BAR(B_DATA), 20480);
          bulk_g2s(sb + SM_V, g_buf + G_VT + c * 20480, 20480, BAR(B_DATA));
          mbar_arrive(BAR(B_GO));
        }
        __syncwarp();
      } else if (warp == 10) {
        if (elect_one()) {
          if (c < 120) bulk_s2g(g_buf + G_MOD + 3840 + 32 * c, sb + SM_RED + 256, 32);
          bulk_commit(); bulk_wait0();
          red_relaxed(C_MOD2);
          mbar_wait(BAR(B_GO), 0);
#pragma unroll
          for (int i = 0; i < 2; i++) tma2d_store(&tmXV, 32 * (c >> 1), 320 * kh + i * 160, sb + SM_X + i * 10240);
          bulk_commit();
        }
        __syncwarp();
      } else if (warp == 11) {
        poll_ge(C_MOD2, (lds32(sb + SM_C0 + 4 * C_MOD2) & ~127u) + 128);
        if (elect_one()) {
          mbar_expect_tx(BAR(B_SB), 2560);
          bulk_g2s(sb + SM_SB, g_buf + G_MOD + 3840, 2560, BAR(B_SB));
          asm volatile("cp.async.bulk.prefetch.L2.global [%0], %1;" ::"l"((const char*)P.wd + c * 17280), "r"(17280) : "memory");
        }
        __syncwarp();
      }
    }
    MARK(5);
    {
      const uint32_t kp = tab + 2048 + g * 32 + q4 * 8;
#pragma unroll
      for (int s = 0; s < 5; s++) { sts64f(kp + 512 * s, T[s][0], T[s][1]); sts64f(kp + 512 * s + 256, T[s][2], T[s][3]); }
#pragma unroll
      for (int o = 16; o; o >>= 1) k2048 += __shfl_xor_sync(0xffffffffu, k2048, o);
      stsf(tab + 2048 + 2560, k2048);
    }
    if (warp == 0) STAMP(2);
    nbar(barid, gsz);
    const float cK0 = 2.0f * dt * scC;
    const float sK = fmaxf(fmaxf(cK0, fabsf(pD)), 1e-30f);
    {
      const float cK = cK0 * rcpf(sK);
      float4 v[3];
#pragma unroll
      for (int k = 0; k < 3; k++) {
        const uint32_t a = cb + O_W + 2048 + min(gtid + k * gsz, 160) * 16;
        const float4 p = lds128f(a), q = lds128f(a + WBS);
        v[k] = make_float4(p.x + q.x, p.y + q.y, p.z + q.z, p.w + q.w);
        if (warp >= 8) {
          const float4 r = lds128f(a + 2 * WBS), t = lds128f(a + 3 * WBS);
          v[k].x += r.x + t.x; v[k].y += r.y + t.y; v[k].z += r.z + t.z; v[k].w += r.w + t.w;
        }
      }
#pragma unroll
      for (int k = 0; k < 3; k++) {
        const int u = gtid + k * gsz;
        const uint32_t o = cb + O_KH + 6 + ((u >> 5) * 128 + (u & 1) * 64 + ((u >> 1) & 15)) * 2;
        const uint32_t w0 = pack_h2(fmaf(v[k].x, cK, u == 0 ? pD * rcpf(sK) : 0.f), v[k].y * cK), w1 = pack_h2(v[k].z * cK, v[k].w * cK);
        if (u <= 160) sts16(o, w0);
        if (u < 160) { sts16(o + 32, w0 >> 16); sts16(o + 64, w1); sts16(o + 96, w1 >> 16); }
      }
      if (gtid == 1) sts64f(cb + O_KH + 1288, 0.f, 0.f);
    }
    nbar(barid, gsz);
    {
      auto kadr = [&](int l) -> uint32_t {
        int rk = l < 256 ? l : min(128 + ((l + ((l >> 1) & 1)) >> 1), 384);
        if ((unsigned)l > 514u) rk = (unsigned)(l - 1027) < 2u ? 512 : 641;
        return cb + O_KH + 6 + rk * 2;
      };
#pragma unroll 1
      for (int i0 = 2 * gtid; i0 < 608; i0 += 6 * gsz) {
        uint32_t kv[3][3];
#pragma unroll
        for (int k = 0; k < 3; k++) {
          const int i = i0 + 2 * k * gsz, x = i < 560 ? i - 16 : i + 448;
          kv[k][0] = lds16(kadr(x - 1)); kv[k][1] = lds16(kadr(x)); kv[k][2] = lds16(kadr(x + 1));
        }
#pragma unroll
        for (int k = 0; k < 3; k++) {
          const int i = i0 + 2 * k * gsz;
          if (i < 608) asm volatile("st.shared.v2.u32 [%0], {%1,%2};" ::"r"(cb + O_PT + i * 4), "r"(kv[k][1] | (kv[k][0] << 16)), "r"(kv[k][2] | (kv[k][1] << 16)) : "memory");
        }
      }
      if (gtid < 18)
        sts128(cb + (gtid < 16 ? (gtid >> 3) * HPL + (gtid & 7) * 16 : gtid == 16 ? O_U3 + 3 * U35 : O_U7 + U79), make_uint4(0, 0, 0, 0));
    }
    if (warp == 0) STAMP(3);
    MARK(6);
    MARK(8);
    mbar_wait(BAR(B_GO), 0);
    float G;
    {
      const float sa = ldg_mod(dch), ca1 = ldg_mod(DM + dch), ga = ldg_mod(2 * DM + dch);
      mbar_wait(BAR(B_DATA), 0);
      if (warp == 0) STAMP(4);
      const uint32_t e = (__float_as_uint(fmaxf(fmaxf(fabsf(sa), fabsf(ca1)), 1e-30f)) & 0x7f800000u) + 0x00800000u;
      const float ish = __uint_as_float(0x7f000000u - e);
      G = ga * __uint_as_float(e) * sK;
      const uint32_t ha = pack_h2(ca1 * ish, ca1 * ish), hb = pack_h2(sa * ish, sa * ish);
      const int par = lane >> 4;
#pragma unroll 1
      for (int m = (lane & 15) + 16 * part; m < 128; m += 16 << lsp) {
        const uint32_t va = sb + SM_V + ch * 4096 + m * 16;
        const uint4 v2 = lds128(va + par * 2048), v1 = lds128(va + (par ? 0 : 2048 - 16)), v0 = lds128(va + par * 2048 - 16);
        const uint32_t a1 = (m | par) ? ha : 0u, b1 = (m | par) ? hb : 0u, a0 = m ? ha : 0u, b0 = m ? hb : 0u;
        uint32_t H[11];
        H[0] = hfma2_h(m ? v0.y : 0u, a0, b0); H[1] = hfma2_h(m ? v0.z : 0u, a0, b0); H[2] = hfma2_h(m ? v0.w : 0u, a0, b0);
        H[3] = hfma2_h(v1.x, a1, b1); H[4] = hfma2_h(v1.y, a1, b1); H[5] = hfma2_h(v1.z, a1, b1); H[6] = hfma2_h(v1.w, a1, b1);
        H[7] = hfma2_h(v2.x, ha, hb); H[8] = hfma2_h(v2.y, ha, hb); H[9] = hfma2_h(v2.z, ha, hb); H[10] = hfma2_h(v2.w, ha, hb);
        sts128(cb + par * HPL + 128 + m * 16, make_uint4(H[7], H[8], H[9], H[10]));
        if (m < 97) {
          uint32_t O[8], W[6];
#pragma unroll
          for (int k = 0; k < 8; k++) O[k] = __byte_perm(H[k], H[k + 1], 0x5432);
#pragma unroll
          for (int k = 0; k < 6; k++) W[k] = hadd2_h(hadd2_h(O[k], O[k + 1]), H[k + 1]);
          const uint32_t u = cb + O_U3 + m * 16;
          sts128(u + (par ? 16 : 2 * U35), make_uint4(W[0], W[1], W[2], W[3]));
#pragma unroll
          for (int k = 2; k < 6; k++) W[k] = hadd2_h(W[k], hadd2_h(H[k], H[k + 2]));
          sts128(u + par * 2 * U35 + U35 + 16, make_uint4(W[2], W[3], W[4], W[5]));
          if (m < 64) {
#pragma unroll
            for (int k = 2; k < 6; k++) W[k] = hadd2_h(W[k], hadd2_h(O[k - 1], O[k + 2]));
            const uint32_t u7 = cb + O_U7 + m * 16;
            sts128(u7 + par * 2 * U79, make_uint4(W[2], W[3], W[4], W[5]));
#pragma unroll
            for (int k = 2; k < 6; k++) W[k] = hadd2_h(W[k], hadd2_h(H[k - 1], H[k + 3]));
            sts128(u7 + U79 + (par ? 16 : 2 * U79), make_uint4(W[2], W[3], W[4], W[5]));
          }
        }
      }
    }
    nbar(barid, gsz);
    if (warp == 0) STAMP(23);
    MARK(9);
    if (warp >= 8) {
      if (warp == 10) {
        if (elect_one()) { bulk_wait0(); red_relaxed(C_XF); }
        __syncwarp();
      }
      mbar_wait(BAR(B_SB), 0);
      mbar_wait(BAR(B_WS), 0);
      if (warp == 8) STAMP(17);
      if (c < 108) {
        const int hw = warp - 8, up = c >= 54;
        const int f = 32 * (up ? c - 54 : c) + 8 * q4;
        const int fh = f >= 864, fl = f - 864 * fh;
        const int tl = fl >> 3, pb = tl >= 4 * TA_;
        const int tb = tl - 4 * TA_, ta = tl - 4 * TA1;
        const int fn = pb ? (tb >> 2) & 3 : ta < 0 ? tl / TA1 : ta / TA2;
        const int nt2 = 2 * (pb ? (tb >> 4) * 4 + (tb & 3) : ta < 0 ? tl - fn * TA1 : TA1 + ta - fn * TA2) + up;
        const int j8 = 4 * fh + fn, rstr = pb ? NB * 16 : NA * 16;
        unsigned char* dst = g_buf + G_WP + j8 * (BLOB_A + BLOB_B) + (pb ? BLOB_A : 0) + nt2 * 128 + g * 16 + 2 * hw * rstr;
        float D[4][4];
#pragma unroll
        for (int i = 0; i < 4; i++) { D[i][0] = D[i][1] = D[i][2] = D[i][3] = 0.f; }
        uint32_t am = sb + SM_WS + (hw * 16 + (lane & 15)) * 64 + (((lane >> 4) ^ ((lane >> 1) & 3)) << 4);
        uint32_t as = sb + SM_WS + (hw * 16 + g) * 64 + ((q4 ^ (g >> 1)) << 4);
        uint32_t aa = sb + SM_SB + ((g & 1) ^ 1) * 1280 + hw * 32 + q4 * 4;
        uint32_t ac = sb + SM_SB + 1280 + (hw * 16 + g) * 2;
#pragma unroll 2
        for (int k2 = 0; k2 < 10; k2++) {
          uint32_t b0, b1, b2, b3, b4, b5, b6, b7;
          const uint32_t a0 = lds32(aa), a2 = lds32(aa + 16);
          ldsm4t(am, b0, b1, b2, b3); ldsm4t(am ^ 32, b4, b5, b6, b7);
          uint4 w = lds128(as), w2 = lds128(as + 512);
          const uint32_t s = lds16(ac) * 0x10001u, s2 = lds16(ac + 16) * 0x10001u;
          mma_bf16(D[0], a0, 0u, a2, 0u, b0, b1); mma_bf16(D[1], a0, 0u, a2, 0u, b2, b3);
          mma_bf16(D[2], a0, 0u, a2, 0u, b4, b5); mma_bf16(D[3], a0, 0u, a2, 0u, b6, b7);
          *(uint4*)(dst) = make_uint4(hmul2_bf(w.x, s), hmul2_bf(w.y, s), hmul2_bf(w.z, s), hmul2_bf(w.w, s));
          *(uint4*)(dst + rstr) = make_uint4(hmul2_bf(w2.x, s2), hmul2_bf(w2.y, s2), hmul2_bf(w2.z, s2), hmul2_bf(w2.w, s2));
          am += 4096; as += 4096; aa += 128; ac += 128; dst += 8 * rstr;
        }
        if (lane < 8) {
#pragma unroll
          for (int i = 0; i < 4; i++) sts64f(sb + SM_RED + 320 + hw * 256 + g * 128 + i * 32 + q4 * 8, D[i][0], D[i][1]);
        }
        nbar(7, 128);
        dst = (unsigned char*)__shfl_sync(0xffffffffu, (unsigned long long)(dst - g * 16 - 2 * hw * rstr), lane >> 3);
        const int rs2 = __shfl_sync(0xffffffffu, rstr, lane >> 3);
        if (hw < 2) {
          const uint32_t r = sb + SM_RED + 320 + ht * 4;
          float v = (ldsf(r) + ldsf(r + 256)) + (ldsf(r + 512) + ldsf(r + 768));
          if (hw == 0) v = -v;
          const uint32_t hi = pack_bf2(v, 0.f), lo = pack_bf2(v - bf_lo(hi), 0.f);
          unsigned short* o = (unsigned short*)(dst + hw * 48) + (lane & 7);
          o[0] = (unsigned short)hi; o[8] = (unsigned short)lo; o[16] = (unsigned short)hi;
        } else if (hw == 2 || (lane & 7) < 2) {
          *(uint4*)(dst + (hw == 2 ? rs2 : 96) + (lane & 7) * 16) = make_uint4(0, 0, 0, 0);
        }
      }
      nbar(7, 128);
      if (warp == 9 && elect_one()) red_release(C_BAR2);
      __syncwarp();
      if (warp == 8) STAMP(18);
    }
    if (warp == 8) {
      poll_ge(C_XF, lds32(sb + SM_C0 + 4 * C_XF) + 128);
      if (elect_one()) { mbar_expect_tx(BAR(B_X), 20480); bulk_g2s(sb + SM_X, g_buf + G_XT + c * 20480, 20480, BAR(B_X)); }
      __syncwarp();
    }
    float acc[16][4];
#pragma unroll
    for (int j = 0; j < 16; j++) { acc[j][0] = acc[j][1] = acc[j][2] = acc[j][3] = 0.f; }
    const uint32_t mrow = ((lane >> 4) * 8 + (lane & 7)) * 16, mpl = (lane >> 3) & 1;
#pragma unroll 1
    for (int s0 = part; s0 < 8; s0 += 1 << lsp) {
      uint32_t Bf[16][2];
      const uint32_t hb = cb + mpl * HPL + 128 + mrow - s0 * 16;
#pragma unroll
      for (int j = 0; j < 16; j += 2) ldsm4(hb + j * 128, Bf[j][0], Bf[j][1], Bf[j + 1][0], Bf[j + 1][1]);
      const uint32_t pa = cb + O_PT + (16 + g - 2 * q4) * 4 + s0 * 64;
      uint32_t Af[6][4];
#pragma unroll
      for (int s1 = 0; s1 < 6; s1++) {
        const int off = s1 < 5 ? s1 * 512 : 560 * 4;
        Af[s1][0] = lds32(pa + off); Af[s1][1] = lds32(pa + off + 32); Af[s1][2] = lds32(pa + off - 32);
        asm volatile("mov.b32 %0, %1;" : "=r"(Af[s1][3]) : "r"(Af[s1][0]));
      }
#pragma unroll
      for (int s1 = 0; s1 < 6; s1++) {
        if (s1 == 4 && s0 >= 2) break;
        const int sh = s1 < 5 ? s1 : 8;
#pragma unroll
        for (int j = sh; j < 16; j++) mma_f16(acc[j], Af[s1][0], Af[s1][1], Af[s1][2], Af[s1][3], Bf[j - sh][0], Bf[j - sh][1]);
      }
    }
    if (warp == 0) STAMP(42);
    MARK(10);
    {
      const int pi = part & 1, r = lane & 7, hf = mpl, sh = lane >> 4;
      uint2 Bw[5];
#pragma unroll
      for (int i = 0; i < 5; i++) {
        const int kap = 32 + 8 * i - 4 * pi + g - q4;
        Bw[i] = lds64(cb + O_KH + (((i == 0 || i == 4) && (unsigned)(kap - 32) > 31u) ? 1288 : 520 + 8 * kap));
      }
      const uint32_t ua = cb + O_U3 + ((hf ^ sh) * 2 + (r & 1)) * U35 + (4 * pi + (r >> 1) + (hf < sh ? 0 : 1)) * 16;
      const bool all = warp < 8; const int sel = part < 2;
#pragma unroll
      for (int h = 0; h < 12; h++) {
        if (all || (h & 1) == sel) {
          uint32_t a0, a1, a2, a3;
          ldsm4t(ua + h * 128, a0, a1, a2, a3);
#pragma unroll
          for (int i = 0; i < 5; i++)
            if (h + 4 + i < 16) mma_f16(acc[h + 4 + i], a0, a1, a2, a3, Bw[i].x, Bw[i].y);
        }
      }
      if (all || !sel) {
        uint32_t B3[8][2];
#pragma unroll
        for (int d = 0; d < 8; d++) {
          const int kap = 64 + 8 * d + g - q4;
          B3[d][0] = lds32(cb + O_KH + ((d == 0 && kap < 64) ? 1288 : 776 + 4 * kap));
          B3[d][1] = lds32(cb + O_KH + ((d == 0 && kap < 68) ? 1288 : 776 + 4 * kap - 16));
        }
        const uint32_t u7 = cb + O_U7 + (hf * 2 + (r & 1)) * U79 + (4 * sh + (r >> 1)) * 16;
#pragma unroll
        for (int G3 = 0; G3 < 8; G3++) {
          if ((G3 & 1) == pi) {
            uint32_t a0, a1, a2, a3;
            ldsm4t(u7 + G3 * 128, a0, a1, a2, a3);
#pragma unroll
            for (int d = 0; d < 8 - G3; d++) mma_f16(acc[G3 + 8 + d], a0, a1, a2, a3, B3[d][0], B3[d][1]);
          }
        }
      }
    }
    if (warp == 0) STAMP(5);
    if (warp == 8) STAMP(24);
    MARK(11);
    MARK(7);
    nbar(barid, gsz);
    if (warp == 0) STAMP(37);
    const uint32_t ax = sb + SM_X + ch * 4096 + mpl * 2048 + mrow;
    auto x1pair = [&](int j, float4 y0, float4 y1) {
      uint32_t r0, r1, r2, r3;
      ldsm4t(ax + j * 128, r0, r1, r2, r3);
      stsm4t(ax + j * 128, pack_bf2(fmaf(G, y0.x, bf_lo(r0)), fmaf(G, y0.y, bf_hi(r0))), pack_bf2(fmaf(G, y0.z, bf_lo(r1)), fmaf(G, y0.w, bf_hi(r1))),
             pack_bf2(fmaf(G, y1.x, bf_lo(r2)), fmaf(G, y1.y, bf_hi(r2))), pack_bf2(fmaf(G, y1.z, bf_lo(r3)), fmaf(G, y1.w, bf_hi(r3))));
    };
    if (warp < 8) {
      if (part) {
#pragma unroll
        for (int j = 0; j < 8; j++)
#pragma unroll
          for (int e = 0; e < 4; e++) { const float t = acc[j][e]; acc[j][e] = acc[j + 8][e]; acc[j + 8][e] = t; }
      }
      const uint32_t a = cb + lane * 16;
#pragma unroll
      for (int j = 0; j < 8; j++) sts128f(a + part * 4096 + j * 512, acc[j + 8][0], acc[j + 8][1], acc[j + 8][2], acc[j + 8][3]);
      mbar_wait(BAR(B_X), 0);
      nbar(barid, gsz);
      if (warp == 0) STAMP(38);
      float4 v[8];
#pragma unroll
      for (int j = 0; j < 8; j++) v[j] = lds128f(a + (part ^ 1) * 4096 + j * 512);
#pragma unroll
      for (int j = 0; j < 8; j += 2)
        x1pair(part * 8 + j, make_float4(acc[j][0] + v[j].x, acc[j][1] + v[j].y, acc[j][2] + v[j].z, acc[j][3] + v[j].w),
               make_float4(acc[j + 1][0] + v[j + 1].x, acc[j + 1][1] + v[j + 1].y, acc[j + 1][2] + v[j + 1].z, acc[j + 1][3] + v[j + 1].w));
    } else {
      const uint32_t a = cb + lane * 16;
#pragma unroll
      for (int j = 0; j < 16; j++) sts128f(a + part * 8192 + j * 512, acc[j][0], acc[j][1], acc[j][2], acc[j][3]);
      mbar_wait(BAR(B_X), 0);
      nbar(barid, gsz);
#pragma unroll 1
      for (int j = part * 4; j < part * 4 + 4; j += 2) {
        float4 v[8];
#pragma unroll
        for (int o = 0; o < 8; o++) v[o] = lds128f(a + j * 512 + (o >> 1) * 8192 + (o & 1) * 512);
        x1pair(j, make_float4((v[0].x + v[2].x) + (v[4].x + v[6].x), (v[0].y + v[2].y) + (v[4].y + v[6].y), (v[0].z + v[2].z) + (v[4].z + v[6].z), (v[0].w + v[2].w) + (v[4].w + v[6].w)),
               make_float4((v[1].x + v[3].x) + (v[5].x + v[7].x), (v[1].y + v[3].y) + (v[5].y + v[7].y), (v[1].z + v[3].z) + (v[5].z + v[7].z), (v[1].w + v[3].w) + (v[5].w + v[7].w)));
      }
    }
    if (warp == 0) STAMP(39);
    if (warp == 8) STAMP(40);
    fence_async_smem();
    nbar(barid, gsz);
    if (part == 0 && elect_one()) {
      bulk_s2g(g_buf + G_X1T + dch * 4096, sb + SM_X + ch * 4096, 4096);
      bulk_commit(); bulk_wait0();
      red_relaxed(C_BAR2);
    }
    if (warp == 8) STAMP(41);
    __syncwarp();
    if (warp == 0) STAMP(6);
  }
  MARK(12);
  if (warp < 8) {
    asm volatile("setmaxnreg.inc.sync.aligned.u32 224;");
    const int wgi = warp >> 2;
    const bool elect = (tid & 127) == 0;
    const int wrow = wgi * 64 + (warp & 3) * 16;
    const uint64_t dA = mkdesc(sb + SM_A + wgi * 8192, 1024, 1024, 1), dX = mkdesc(sb + SM_AX + wgi * 2048, 1024, 1024, 1);
    uint32_t pk[60];
    {
      float acc[NA / 2];
      const uint64_t dB = mkdesc(sb + SM_B, (NA / 8) * 128, 128, 0);
#pragma unroll 1
      for (int k4 = 0; k4 < 5; k4++) {
#pragma unroll
        for (int s = 0; s < 4; s++) {
          CSTAMP(k4 * 4 + s);
          if (!(s & 1)) mbar_wait(BAR(B_FULLA + 2 * k4 + (s >> 1)), 0);
          mbar_wait(BAR(B_FULL + s), k4 & 1);
          CSTAMP(128 + k4 * 4 + s);
          if (s == 0 && k4 == 0 && warp == 0) STAMP(8);
          wg_fence();
          const uint64_t a = dA + (uint32_t)(k4 * 2048 + (s >> 1) * 1024 + (s & 1) * 256), b = dB + s * (BST >> 4);
          WG<NA>::ss<1, 1>(acc, a, b, s | k4);
          WG<NA>::ss<1, 1>(acc, a + 128, b + (NA / 8) * 16, 1);
          wg_commit();
          wg_wait<1>();
          mbar_arrive_if(BAR(B_EMPTY + ((s + 3) & 3)), elect && (s | k4));
        }
      }
      if (warp == 0) STAMP(35);
      mbar_wait(BAR(B_STATS), 0);
      if (warp == 0) STAMP(36);
      mbar_wait(BAR(B_FULL), 1);
      wg_fence();
      WG<NA>::ss<1, 1>(acc, dX, dB, 1);
      wg_commit();
      wg_wait<0>();
      mbar_arrive_if(BAR(B_EMPTY + 3), elect); mbar_arrive_if(BAR(B_EMPTY), elect);
#pragma unroll
      for (int i = 0; i < NA / 4; i++) pk[i] = pack_bf2(acc[2 * i], acc[2 * i + 1]);
    }
    if (warp == 0) STAMP(9);
    MARK(13);
    const float r0 = ldsf(sb + SM_ST2 + (wrow + g) * 4), r1 = ldsf(sb + SM_ST2 + (wrow + g + 8) * 4);
    const float ga0 = 0.7978845608f * r0, gb0 = (0.7978845608f * 0.044715f) * r0 * r0 * r0, gc0 = 0.5f * r0 * r0;
    const float ga1 = 0.7978845608f * r1, gb1 = (0.7978845608f * 0.044715f) * r1 * r1 * r1, gc1 = 0.5f * r1 * r1;
    uint32_t hst = sb + (wrow >> 3) * 128 + lane * 4;
    auto slice2 = [&](int i, int n) {
#pragma unroll
      for (int e = 0; e < 4; e++) {
        if (2 * i + (e >> 1) < n) {
          const uint32_t pg = pk[8 * i + (e >> 1) * 4 + (e & 1)], pu = pk[8 * i + (e >> 1) * 4 + 2 + (e & 1)];
          const float c0 = (e & 1) ? ga1 : ga0, c1 = (e & 1) ? gb1 : gb0, c2 = (e & 1) ? gc1 : gc0;
          const float a0 = bf_lo(pg), a1 = bf_hi(pg);
          const float t0 = tanhf_(a0 * fmaf(a0 * a0, c1, c0)), t1 = tanhf_(a1 * fmaf(a1 * a1, c1, c0));
          sts32(hst + i * 4096 + (e >> 1) * 2048 + (e & 1) * 128, hmul2_bf(hmul2_bf(pg, pu), pack_bf2(fmaf(t0, c2, c2), fmaf(t1, c2, c2))));
        }
      }
      __syncwarp();
      mbar_arrive_if(BAR(B_H + i + (n == TB_ ? 8 : 0)), lane == 0);
    };
    {
      float acc[NB / 2];
      const uint64_t dB = mkdesc(sb + SM_B, (NB / 8) * 128, 128, 0);
      mbar_test(BAR(B_FULL + 12 + 2), 0);
#pragma unroll
      for (int ks = 0; ks < 20; ks++) {
        const int s = (ks + 2) % 5;
        const uint64_t a = dA + ((ks >> 1) * 1024 + (ks & 1) * 256), b = dB + s * (BS2 >> 4);
        CSTAMP(20 + ks);
        mbar_finish(BAR(B_FULL + 12 + s), (ks / 5) & 1);
        CSTAMP(128 + 20 + ks);
        wg_fence();
        WG<NB>::ss<1, 1>(acc, a, b, ks);
        WG<NB>::ss<1, 1>(acc, a + 128, b + (NB / 8) * 16, 1);
        wg_commit();
        mbar_test(BAR(B_FULL + 12 + (ks + 3) % 5), ((ks + 1) / 5) & 1);
        if ((ks & 1) && ks >= 3 && ks < TA_ + 3) {
          if (ks == 3 || ks == 11) mbar_wait(BAR(B_FREEA + (ks == 11)), 0);
          slice2((ks - 3) >> 1, TA_);
        }
        wg_wait<1>();
        if (ks) mbar_arrive_if(BAR(B_EMPTY + 12 + (ks + 1) % 5), elect);
        if (ks && !(ks & 1)) mbar_arrive_if(BAR(B_FREEA - 1 + (ks >> 1)), elect);
      }
      mbar_finish(BAR(B_FULL + 12 + 2), 0);
      wg_fence();
      WG<NB>::ss<1, 1>(acc, dX, dB + 2 * (BS2 >> 4), 1);
      wg_commit();
      wg_wait<0>();
      mbar_arrive_if(BAR(B_FREEA + 9), elect);
#pragma unroll
      for (int i = 0; i < NB / 4; i++) pk[i] = pack_bf2(acc[2 * i], acc[2 * i + 1]);
    }
    if (warp == 0) STAMP(10);
    MARK(14);
    float acc[80];
    {
      const uint64_t dH = mkdesc(sb + wgi * 1024, 2048, 128, 0), dW = mkdesc(sb + 8192, 2560, 128, 0);
      hst += SM_XR;
      mbar_test(BAR(B_FULL + 4 + 2), 0);
      auto stage2 = [&](int s2, bool head) {
        const int s = (s2 + 2) & 7;
        const uint32_t o = s * (SLOT2 >> 4);
        CSTAMP(40 + s2);
        mbar_finish(BAR(B_FULL + 4 + s), (s2 >> 3) & 1);
        CSTAMP(128 + 40 + s2);
        wg_fence();
        WG<160>::ss<0, 1>(acc, dH + o, dW + o, s2);
        WG<160>::ss<0, 1>(acc, dH + o + 256, dW + o + 320, 1);
        wg_commit();
        mbar_test(BAR(B_FULL + 4 + ((s2 + 3) & 7)), ((s2 + 1) >> 3) & 1);
        if (head && !(s2 & 1)) {
          if (s2 == 0) mbar_wait(BAR(B_FREEA + 9), 0);
          slice2(s2 >> 1, TB_);
        }
        wg_wait<1>();
        mbar_arrive_if(BAR(B_EMPTY + 4 + ((s + 7) & 7)), elect && s2);
      };
#pragma unroll
      for (int s2 = 0; s2 < TB_ - 1; s2++) stage2(s2, true);
#pragma unroll 1
      for (int s2 = TB_ - 1; s2 < S2; s2 += 2) { stage2(s2, false); stage2(s2 + 1, false); }
      wg_wait<0>();
    }
    if (warp == 0) STAMP(11);
    MARK(15);
    const uint32_t xo = warp * 5120 + lane * 16;
    {
      mbar_wait(BAR(B_EMPTY + 4 + 1), 0);
#pragma unroll
      for (int i = 0; i < 10; i++) sts128f(sb + SM_XS + xo + i * 512, acc[40 + 4 * i], acc[41 + 4 * i], acc[42 + 4 * i], acc[43 + 4 * i]);
      fence_async_smem();
      mbar_wait_bounded(BAR(B_XRDY), 0);
      __syncwarp();
      if (elect_one())
        asm volatile("cp.async.bulk.shared::cluster.shared::cta.mbarrier::complete_tx::bytes [%0], [%1], 5120, [%2];"
                     ::"r"(mapa(sb + warp * 5120 + SM_XR, kh ^ 1)), "r"(sb + warp * 5120 + SM_XS), "r"(mapa(BAR(B_XFULL), kh ^ 1)) : "memory");
      __syncwarp();
    }
    const int col0 = 160 * n4 + 80 * kh;
    const int mi = lane >> 3, rr = lane & 7;
    const uint32_t ar = sb + SM_RES + wgi * 10240 + ((mi >> 1) * 8 + rr) * 128 + ((((warp & 3) * 2 + (mi & 1)) ^ rr) << 4);
    const uint32_t stg = sb + warp * 2816;
    const uint32_t as = stg + ((mi & 1) * 8 + rr) * 176 + (mi >> 1) * 16, ax = sb + xo, ag = sb + SM_GB + q4 * 4;
    mbar_wait(BAR(B_RES), 0);
    uint32_t xr[5][4], gbw[10];
#pragma unroll
    for (int i = 0; i < 5; i++) {
      gbw[2 * i] = lds32(ag + i * 32); gbw[2 * i + 1] = lds32(ag + i * 32 + 16);
      ldsm4t(ar + i * 2048, xr[i][0], xr[i][1], xr[i][2], xr[i][3]);
    }
    if (warp == 0) STAMP(13);
    const int row = lane >> 1, mr = (warp & 3) * 16 + row;
    __nv_bfloat16* const op = P.out + (128 * mt + 16 * (mr >> 3) + 8 * wgi + (mr & 7)) * DM + col0 + (lane & 1) * 40;
#pragma unroll 1
    for (int it = 0; it < 2; it++) {
      if (it) { mbar_wait_bounded(BAR(B_XFULL), 0); if (warp == 0) STAMP(14); }
      float4 pv[10];
#pragma unroll
      for (int i = 0; i < 10; i++) pv[i] = lds128f(ax + i * 512 + SM_XR);
#pragma unroll
      for (int i = 0; i < 5; i++) {
        const uint32_t gb0 = gbw[2 * i], gb1 = gbw[2 * i + 1];
        const float4 p0 = pv[2 * i], p2 = pv[2 * i + 1];
        stsm4(as + i * 32, pack_bf2(fmaf(bf_lo(gb0), acc[8 * i] + p0.x, bf_lo(xr[i][0])), fmaf(bf_hi(gb0), acc[8 * i + 1] + p0.y, bf_hi(xr[i][0]))),
              pack_bf2(fmaf(bf_lo(gb0), acc[8 * i + 2] + p0.z, bf_lo(xr[i][1])), fmaf(bf_hi(gb0), acc[8 * i + 3] + p0.w, bf_hi(xr[i][1]))),
              pack_bf2(fmaf(bf_lo(gb1), acc[8 * i + 4] + p2.x, bf_lo(xr[i][2])), fmaf(bf_hi(gb1), acc[8 * i + 5] + p2.y, bf_hi(xr[i][2]))),
              pack_bf2(fmaf(bf_lo(gb1), acc[8 * i + 6] + p2.z, bf_lo(xr[i][3])), fmaf(bf_hi(gb1), acc[8 * i + 7] + p2.w, bf_hi(xr[i][3]))));
      }
      __syncwarp();
      uint4 v[5];
#pragma unroll
      for (int i = 0; i < 5; i++) v[i] = lds128(stg + row * 176 + (lane & 1) * 80 + i * 16);
      if (it) {
#pragma unroll
        for (int i = 0; i < 5; i++) *(uint4*)(op + i * 8) = v[i];
      }
      __syncwarp();
    }
    if (lane == 0) mbar_arrive(BAR(B_DONE));
    if (warp == 0) STAMP(12);
  } else {
    asm volatile("setmaxnreg.dec.sync.aligned.u32 56;");
    auto ln2_stats = [&]() {
      float s1[8], s2[8];
#pragma unroll
      for (int i = 0; i < 8; i++) { s1[i] = 0.f; s2[i] = 0.f; }
      const int r4 = (lane >> 3) + (warp & 2) * 2;
      const uint32_t a = sb + SM_A + kh * 8192 + r4 * 128 + (((lane & 7) ^ r4) << 4);
#pragma unroll 1
      for (int k = 0; k < 20; k++) {
        if (!(k & 1)) mbar_wait(BAR(B_FULLA + (k >> 1)), 0);
        uint4 v[4];
#pragma unroll
        for (int i = 0; i < 4; i++) v[i] = lds128(a + (k >> 1) * 16384 + (k & 1) * 4096 + i * 1024);
#pragma unroll
        for (int i = 0; i < 4; i++) {
          const uint32_t w[4] = {v[i].x, v[i].y, v[i].z, v[i].w};
#pragma unroll
          for (int e = 0; e < 4; e++) {
            const float x0 = bf_lo(w[e]), x1 = bf_hi(w[e]);
            s1[2 * e] += x0; s2[2 * e] = fmaf(x0, x0, s2[2 * e]); s1[2 * e + 1] += x1; s2[2 * e + 1] = fmaf(x1, x1, s2[2 * e + 1]);
          }
        }
      }
#pragma unroll 1
      for (int o = 8; o < 32; o <<= 1) {
#pragma unroll
        for (int i = 0; i < 8; i++) { s1[i] += __shfl_xor_sync(0xffffffffu, s1[i], o); s2[i] += __shfl_xor_sync(0xffffffffu, s2[i], o); }
      }
      const int e = lane >> 3;
      float a0 = e == 0 ? s1[0] : e == 1 ? s1[2] : e == 2 ? s1[4] : s1[6], b0 = e == 0 ? s2[0] : e == 1 ? s2[2] : e == 2 ? s2[4] : s2[6];
      float a1 = e == 0 ? s1[1] : e == 1 ? s1[3] : e == 2 ? s1[5] : s1[7], b1 = e == 0 ? s2[1] : e == 1 ? s2[3] : e == 2 ? s2[5] : s2[7];
      const uint32_t t = sb + SM_LN2 + lane * 16;
      if (warp == 11) sts128f(t, a0, b0, a1, b1);
      nbar(10, 64);
      if (warp == 9) {
        const float4 o = lds128f(t);
        a0 = (a0 + o.x) * (1.0f / DM); a1 = (a1 + o.z) * (1.0f / DM);
        b0 = fmaxf(fmaf(b0 + o.y, 1.0f / DM, -a0 * a0), 0.f) + 1e-5f; b1 = fmaxf(fmaf(b1 + o.w, 1.0f / DM, -a1 * a1), 0.f) + 1e-5f;
        const uint32_t d = sb + SM_RED + kh * 512 + (lane & 7) * 64 + e * 16;
        sts128f(d, a0, b0, a1, b1);
        asm volatile("st.async.weak.shared::cluster.mbarrier::complete_tx::bytes.v4.f32 [%0], {%1,%2,%3,%4}, [%5];"
                     ::"r"(mapa(d, kh ^ 1)), "f"(a0), "f"(b0), "f"(a1), "f"(b1), "r"(mapa(BAR(B_ST), kh ^ 1)) : "memory");
        __syncwarp();
        if (elect_one()) mbar_expect_tx(BAR(B_ST), 512);
        __syncwarp();
      }
    };
    if (warp == 8) {
      const unsigned char* src = g_buf + G_WP + jj * (BLOB_A + BLOB_B);
      poll_ge(C_BAR2, lds32(sb + SM_C0 + 4 * C_BAR2) + 768);
      STAMP(19);
      if (elect_one()) {
#pragma unroll
        for (int k = 0; k < 4; k++) {
          if (k < 3) { mbar_expect_tx(BAR(B_FULLA + k), 16384); tma3d_mc(sb + SM_A + k * 16384 + kh * 8192, &tmX1, 64 * mt, 64 * k, kh, BAR(B_FULLA + k)); }
          mbar_expect_tx(BAR(B_FULL + k), BST); bulk_g2s(sb + SM_B + k * BST, src + k * BST, BST, BAR(B_FULL + k));
        }
      }
      __syncwarp();
      src += 4 * BST;
#pragma unroll 1
      for (int kb = 4; kb < 21; kb++) {
        const int s = kb & 3;
        const uint32_t bytes = kb < 20 ? BST : BST / 2;
        mbar_wait(BAR(B_EMPTY + s), ((kb >> 2) & 1) ^ 1);
        CSTAMP(256 + min(kb, 19));
        if (elect_one()) {
          mbar_expect_tx(BAR(B_FULL + s), bytes);
          bulk_g2s(sb + SM_B + s * BST, src, bytes, BAR(B_FULL + s));
          if (kb < 11) { mbar_expect_tx(BAR(B_FULLA - 1 + kb), 16384); tma3d_mc(sb + SM_A + (kb - 1) * 16384 + kh * 8192, &tmX1, 64 * mt, 64 * (kb - 1), kh, BAR(B_FULLA - 1 + kb)); }
        }
        src += bytes;
      }
#pragma unroll 1
      for (int r = 0; r < 5; r++) {
#pragma unroll
        for (int i = 0; i < 5; i++) {
          const int s = (i + 2) % 5;
          if (r == 4 && i) break;
          mbar_wait(r ? BAR(B_EMPTY + 12 + s) : BAR(B_EMPTY + (i == 0 ? 2 : i < 3 ? 3 : 0)), r ? (r - 1) & 1 : i >= 3);
          CSTAMP(256 + 20 + min(5 * r + i, 19));
          if (elect_one()) {
            mbar_expect_tx(BAR(B_FULL + 12 + s), r < 4 ? BS2 : BS2 / 2);
            bulk_g2s(sb + SM_B + s * BS2, src + i * BS2, r < 4 ? BS2 : BS2 / 2, BAR(B_FULL + 12 + s));
          }
        }
        src += 5 * BS2;
      }
#pragma unroll 1
      for (int seg = 2; seg < 5; seg++) {
        poll_ge(C_MT + 32 * mt + C_H + 8 * kh + seg, lds32(sb + SM_C0 + 64 + 4 * (C_H + 8 * kh + seg)) + 4);
        mbar_arrive_if(BAR(B_SEG + seg), lane == 0);
      }
    } else if (warp == 9) {
#pragma unroll
      for (int i = 0; i < 4; i++) sts128(sb + SM_AX + (i >> 1) * 2048 + 1024 + (i & 1) * 512 + lane * 16, make_uint4(0, 0, 0, 0));
      if (elect_one()) {
        mbar_expect_tx(BAR(B_GB), 160);
        bulk_g2s(sb + SM_GB, g_buf + G_MOD + (5 * DM + 160 * n4 + 80 * kh) * 2, 160, BAR(B_GB));
      }
      ln2_stats();
      mbar_wait_bounded(BAR(B_ST), 0);
      const float4 u = lds128f(sb + SM_RED + lane * 32), w = lds128f(sb + SM_RED + lane * 32 + 16);
      const float ra = rsqf(u.y), rb = rsqf(u.w), rc = rsqf(w.y), rd = rsqf(w.w);
      sts128f(sb + SM_ST2 + lane * 16, ra, rb, rc, rd);
      const uint32_t mh0 = pack_bf2(u.x, u.z), mh1 = pack_bf2(w.x, w.z);
      const uint32_t ml0 = pack_bf2(u.x - bf_lo(mh0), u.z - bf_hi(mh0)), ml1 = pack_bf2(w.x - bf_lo(mh1), w.z - bf_hi(mh1));
      const float sa_ = u.y * ra, sb_ = u.w * rb, sc_ = w.y * rc, sd_ = w.w * rd;
      const uint32_t sh0 = pack_bf2(sa_, sb_), sh1 = pack_bf2(sc_, sd_);
      const uint32_t sl0 = pack_bf2(sa_ - bf_lo(sh0), sb_ - bf_hi(sh0)), sl1 = pack_bf2(sc_ - bf_lo(sh1), sd_ - bf_hi(sh1));
      const uint32_t ao = sb + SM_AX + (lane >> 4) * 2048 + (lane & 1) * 8, chk = (lane & 15) >> 1;
#pragma unroll
      for (int k = 0; k < 8; k++) {
        const uint32_t v0 = k < 2 ? mh0 : k == 2 ? ml0 : k < 5 ? sh0 : k == 5 ? sl0 : 0u;
        const uint32_t v1 = k < 2 ? mh1 : k == 2 ? ml1 : k < 5 ? sh1 : k == 5 ? sl1 : 0u;
        asm volatile("st.shared.v2.u32 [%0], {%1,%2};" ::"r"(ao + k * 128 + ((chk ^ k) << 4)), "r"(v0), "r"(v1) : "memory");
      }
      fence_async_smem();
      mbar_wait(BAR(B_GB), 0);
      __syncwarp();
      mbar_arrive_if(BAR(B_STATS), lane == 0);
      unsigned char* const hg = g_buf + G_H + (mt * 216 + 108 * kh) * 2048;
#pragma unroll 1
      for (int i = 0; i < 14; i++) {
        const int tile = i < 4 ? n4 * TA1 + 2 * i : i < 8 ? 4 * TA1 + n4 * TA2 + 2 * i - TA1 : 4 * TA_ + ((i - 8) >> 1) * 16 + n4 * TB1 + (i & 1) * 2;
        mbar_wait(BAR(B_H + i), 0);
        fence_async_smem();
        if (elect_one()) {
          bulk_s2g(hg + tile * 2048, sb + (i < 8 ? i * 4096 : SM_XR + (i - 8) * 4096), i == 7 ? 2048 : 4096);
          bulk_commit();
          if (i == 3 || (i >= 7 && (i & 1))) {
            CSTAMP(500 + (i == 3 ? 0 : i - 5));
            bulk_wait0();
            red_relaxed(C_MT + 32 * mt + C_H + 8 * kh + (i == 3 ? 0 : (i - 5) >> 1));
            CSTAMP(501 + (i == 3 ? 0 : i - 5));
            if (i == 7) mbar_arrive(BAR(B_STG));
            if (i == 13) asm volatile("mbarrier.arrive.shared::cluster.b64 _, [%0];" ::"r"(mapa(BAR(B_XRDY), kh ^ 1)) : "memory");
          }
        }
        __syncwarp();
      }
      mbar_wait_bounded(BAR(B_DONE), 0);
    } else if (warp == 10) {
      if (c < 108) {
        const unsigned char* src = (const unsigned char*)P.wd + (16 * c + g) * 1280 + q4 * 16;
        const int rg = 2 * c - (c >= 54 ? 108 : 0);
        unsigned char* dst = g_buf + G_WD + ((c >= 54 ? 4 * S2 : 0) + (rg >> 2)) * 10240 + (rg & 3) * 2560 + g * 16;
        const int rot = c >= 54 ? 10 : 0;
        mbar_wait(BAR(B_FULLA + 3), 0);
#pragma unroll 1
        for (int it = 0; it < 8; it++) {
          uint4 v[5];
#pragma unroll
          for (int k = 0; k < 5; k++) v[k] = __ldg((const uint4*)(src + (it >> 2) * 10240 + (it & 3) * 320 + k * 64));
#pragma unroll
          for (int k = 0; k < 5; k++) *(uint4*)(dst + (it >> 2) * 2560 + (it & 3) * (S2 * 10240) + ((4 * k + q4 + rot) % 20) * 128) = v[k];
        }
      }
      __syncwarp();
      if (elect_one()) red_release(C_WD);
      const unsigned char* hsrc = g_buf + G_H + (mt * 216 + 108 * kh) * 2048;
      int s2 = 0;
#pragma unroll 1
      for (int seg = 0; seg < 5; seg++) {
        if (seg < 2) poll_ge(C_MT + 32 * mt + C_H + 8 * kh + seg, lds32(sb + SM_C0 + 64 + 4 * (C_H + 8 * kh + seg)) + 4);
        else { mbar_wait(BAR(B_SEG + seg), 0); fence_async(); }
        const int send = seg == 0 ? TA1 : TA_ + (seg - 1) * TB1;
#pragma unroll 1
        for (; s2 < send; s2++) {
          const int s = (s2 + 2) & 7;
          const uint32_t fb = BAR(B_FULL + 4 + s);
          mbar_wait(s2 < 6 ? BAR(B_FREEA + s2 + 3) : s2 < 8 ? BAR(B_STG) : fb + EMP, s2 < 8 ? 0 : ((s2 >> 3) & 1) ^ 1);
          CSTAMP(256 + 40 + s2);
          if (elect_one()) bulk_g2s(sb + s * SLOT2, hsrc + s2 * 8192, 8192, fb);
        }
      }
    } else {
      ln2_stats();
      if (elect_one()) mbar_expect_tx(BAR(B_XFULL), 40960);
      const unsigned char* src = g_buf + G_WD + jj * S2 * 10240;
      poll_ge(C_WD, lds32(sb + SM_C0 + 4 * C_WD) + 128);
#pragma unroll 1
      for (int s2 = 0; s2 < S2; s2++) {
        const int s = (s2 + 2) & 7;
        const uint32_t fb = BAR(B_FULL + 4 + s);
        mbar_wait(s2 < 6 ? BAR(B_FREEA + s2 + 3) : s2 < 8 ? BAR(B_STG) : fb + EMP, s2 < 8 ? 0 : ((s2 >> 3) & 1) ^ 1);
        if (elect_one()) {
          mbar_expect_tx(fb, SLOT2);
          bulk_g2s(sb + s * SLOT2 + 8192, src + s2 * 10240, 10240, fb);
        }
        if (s2 == 7) {
          mbar_wait(BAR(B_FREEA + 9), 0);
          if (elect_one()) {
            mbar_expect_tx(BAR(B_RES), 20480);
            tma3d(sb + SM_RES, &tmRes, 64 * mt, 160 * n4 + 80 * kh, 0, BAR(B_RES));
          }
        }
      }
    }
  }
}

typedef CUresult (*EncFn)(CUtensorMap*, CUtensorMapDataType, cuuint32_t, void*, const cuuint64_t*, const cuuint64_t*,
                          const cuuint32_t*, const cuuint32_t*, CUtensorMapInterleave, CUtensorMapSwizzle,
                          CUtensorMapL2promotion, CUtensorMapFloatOOBfill);

void enc2d(EncFn enc, CUtensorMap* tm, const void* base, int cols, int rows, int bc, int br, CUtensorMapSwizzle sw) {
  cuuint64_t dims[2] = {(cuuint64_t)cols, (cuuint64_t)rows}; cuuint64_t str[1] = {(cuuint64_t)cols * 2}; cuuint32_t es[2] = {1, 1};
  cuuint32_t box[2] = {(cuuint32_t)bc, (cuuint32_t)br};
  enc(tm, CU_TENSOR_MAP_DATA_TYPE_BFLOAT16, 2, (void*)base, dims, str, box, es, CU_TENSOR_MAP_INTERLEAVE_NONE, sw,
      CU_TENSOR_MAP_L2_PROMOTION_NONE, CU_TENSOR_MAP_FLOAT_OOB_FILL_NONE);
}

}

extern "C" void kernel_launch(void* const* d_in, const int* in_sizes, int n_in, void* d_out, int out_size) {
  (void)in_sizes; (void)n_in; (void)out_size;
  static EncFn enc = nullptr;
  static unsigned char* gb = nullptr;
  if (!enc) {
    void* fn = nullptr; cudaDriverEntryPointQueryResult qr;
    cudaGetDriverEntryPoint("cuTensorMapEncodeTiled", &fn, cudaEnableDefault, &qr);
    enc = (EncFn)fn;
    cudaGetSymbolAddress((void**)&gb, g_buf);
    cudaFuncSetAttribute(fused_kernel, cudaFuncAttributeMaxDynamicSharedMemorySize, SMEM_BYTES);
  }
  Params P;
  P.x = (const __nv_bfloat16*)d_in[0]; P.logA = (const __nv_bfloat16*)d_in[1]; P.Aim = (const __nv_bfloat16*)d_in[2];
  P.Cre = (const __nv_bfloat16*)d_in[3]; P.Cim = (const __nv_bfloat16*)d_in[4]; P.logdt = (const __nv_bfloat16*)d_in[5];
  P.Dskip = (const __nv_bfloat16*)d_in[6]; P.wd = (const __nv_bfloat16*)d_in[10]; P.cvec = (const __nv_bfloat16*)d_in[11];
  P.wmod = (const __nv_bfloat16*)d_in[12]; P.wg = (const __nv_bfloat16*)d_in[8]; P.wu = (const __nv_bfloat16*)d_in[9];
  P.out = (__nv_bfloat16*)d_out;
  CUtensorMap tmX1, tmRes, tmXV, tmX, tmWm, tmWg, tmWu;
  enc2d(enc, &tmWm, d_in[12], 6 * DM, DM, 16, 160, CU_TENSOR_MAP_SWIZZLE_NONE);
  enc2d(enc, &tmWg, d_in[8], DF, DM, 32, 160, CU_TENSOR_MAP_SWIZZLE_64B);
  enc2d(enc, &tmWu, d_in[9], DF, DM, 32, 160, CU_TENSOR_MAP_SWIZZLE_64B);
  enc2d(enc, &tmXV, gb + G_XT, LSEQ, 2 * DM, 32, 160, CU_TENSOR_MAP_SWIZZLE_64B);
  {
    cuuint64_t dims[5] = {64, 8, 128, 10, 2}; cuuint64_t str[4] = {1280, 20480, 128, 10240}; cuuint32_t es[5] = {1, 1, 1, 1, 1};
    cuuint32_t box[5] = {64, 8, 4, 10, 1};
    enc(&tmX, CU_TENSOR_MAP_DATA_TYPE_BFLOAT16, 5, d_in[0], dims, str, box, es, CU_TENSOR_MAP_INTERLEAVE_NONE,
        CU_TENSOR_MAP_SWIZZLE_128B, CU_TENSOR_MAP_L2_PROMOTION_NONE, CU_TENSOR_MAP_FLOAT_OOB_FILL_NONE);
  }
  for (int i = 0; i < 2; i++) {
    cuuint64_t dims[3] = {1024, DM, 2}; cuuint64_t str[2] = {LSEQ * 2, 2048}; cuuint32_t es[3] = {1, 1, 1};
    cuuint32_t box[3] = {64, (cuuint32_t)(i ? 80 : 64), (cuuint32_t)(i ? 2 : 1)};
    enc(i ? &tmRes : &tmX1, CU_TENSOR_MAP_DATA_TYPE_BFLOAT16, 3, gb + G_X1T, dims, str, box, es, CU_TENSOR_MAP_INTERLEAVE_NONE,
        CU_TENSOR_MAP_SWIZZLE_128B, CU_TENSOR_MAP_L2_PROMOTION_NONE, CU_TENSOR_MAP_FLOAT_OOB_FILL_NONE);
  }
  fused_kernel<<<NCTA, NTHR, SMEM_BYTES, cudaStreamPerThread>>>(P, tmX1, tmRes, tmXV, tmX, tmWm, tmWg, tmWu);
}
```
